```python
import torch

def _softmax(x, axis=-1):
    return torch.softmax(x, dim=axis)
def _gelu(x):
    return torch.nn.functional.gelu(x, approximate="tanh")
def _silu(x):
    return torch.nn.functional.silu(x)
def _sigmoid(x):
    return torch.sigmoid(x)
def _layernorm(x, axis=-1, eps=1e-5):
    m = x.mean(dim=axis, keepdim=True)
    v = x.var(dim=axis, keepdim=True, unbiased=False)
    return (x - m) / torch.sqrt(v + eps)
def _scatter_add(tgt, idx, src, axis=0):
    return tgt.clone().index_add_(axis, idx, src)
def _segment_sum(src, seg, n):
    out = torch.zeros((n,) + src.shape[1:], dtype=src.dtype)
    return out.index_add_(0, seg, src)
def _pad(x, pw):
    flat = tuple(v for pair in reversed(pw) for v in pair)
    return torch.nn.functional.pad(x, flat)

kernel_name = 'concat_heads__linear_attn_block__softmax_full_mha__prompt'

def setup_inputs():

    _w = (lambda a: (lambda t: t.to(torch.bfloat16) if t.is_floating_point() else t)(torch.as_tensor(a)))
    def _A_setup():
        B, S, D = 1, 2048, 448
        return {
            "x": _w((lambda *s: torch.randn(*s, dtype=torch.bfloat16) * 0.05)(B, S, D)),
            "wqkv": _w((lambda *s: torch.randn(*s, dtype=torch.bfloat16) * 1.6)(D, 3 * D)),
            "wo": _w((lambda *s: torch.randn(*s, dtype=torch.bfloat16) * 0.05)(D, D)),
        }
    _A_in = _A_setup()

    def _B_setup():
        B, S, D = 1, 2048, 448
        return {
            "x": _w((lambda *s: torch.randn(*s, dtype=torch.bfloat16) * 0.2)(B, S, D)),
            "wqkv": _w((lambda *s: torch.randn(*s, dtype=torch.bfloat16) * 0.2)(D, 3 * D)),
            "wo": _w((lambda *s: torch.randn(*s, dtype=torch.bfloat16) * 0.05)(D, D)),
        }
    _B_in = _B_setup()

    return {
        "A_x": _A_in["x"],
        "A_wqkv": _A_in["wqkv"],
        "A_wo": _A_in["wo"],
        "B_x": _B_in["x"],
        "B_wqkv": _B_in["wqkv"],
        "B_wo": _B_in["wo"],
    }

def reference(A_x, A_wqkv, A_wo, B_x, B_wqkv, B_wo):
    def _A_ref(x, wqkv, wo):
        B, S, D = x.shape
        H = 16; Dh = D // H
        qkv = (lambda x, *d: x.permute(*d))((x @ wqkv).reshape(B, S, 3, H, Dh), 2, 0, 3, 1, 4)
        q, k, v = qkv[0], qkv[1], qkv[2]
        phi = lambda t: torch.where(t > 0, t + 1, torch.exp(t)) + 1e-6
        pq, pk = phi(q), phi(k)
        kv = torch.einsum("bhsd,bhse->bhde", pk, v)
        z = torch.einsum("bhsd->bhd", pk)
        num = torch.einsum("bhqd,bhde->bhqe", pq, kv)
        den = torch.einsum("bhqd,bhd->bhq", pq, z)[..., None] + 1e-6
        o = num / den
        return (lambda x, *d: x.permute(*d))(o, 0, 2, 1, 3).reshape(B, S, D) @ wo

    def _B_ref(x, wqkv, wo):
        B, S, D = x.shape
        H = 16; Dh = D // H
        qkv = (lambda x, *d: x.permute(*d))((x @ wqkv).reshape(B, S, 3, H, Dh), 2, 0, 3, 1, 4)
        q, k, v = qkv[0], qkv[1], qkv[2]
        scale = Dh ** -0.5
        scores = torch.einsum("bhqd,bhkd->bhqk", q, k) * scale
        p = _softmax(scores, axis=-1)
        o = torch.einsum("bhqk,bhkd->bhqd", p, v)
        return (lambda x, *d: x.permute(*d))(o, 0, 2, 1, 3).reshape(B, S, D) @ wo

    a = _A_ref(A_x, A_wqkv, A_wo)
    b = _B_ref(B_x, B_wqkv, B_wo)
    return torch.concatenate([a, b], axis=-1)
```

```cpp
#include <cuda.h>
#include <cuda_runtime.h>
#include <cuda_bf16.h>
#include <stdint.h>

namespace {

constexpr int SEQ = 2048, DM = 448;
constexpr int NCTA = 128;

constexpr uint32_t KV_SLOT   = 16384;
constexpr int      KV_SLOTS  = 5;
constexpr uint32_t OFF_KV    = 0;
constexpr uint32_t OFF_MISC  = 81920;
constexpr uint32_t OFF_A     = 98304;
constexpr uint32_t OFF_B1    = 65536;
constexpr uint32_t B1_STAGE  = 40960;
constexpr uint32_t A_STAGE   = 24576;
constexpr uint32_t OFF_PQ    = OFF_A + 73728;
constexpr uint32_t OFF_PK    = OFF_A + 90112;
constexpr uint32_t OFF_AV    = OFF_A + 106496;
constexpr uint32_t OFF_KVB   = OFF_A + 122880;
constexpr uint32_t OFF_OUTB  = OFF_A + 114688;
constexpr uint32_t OFF_BAR   = 229376;
constexpr uint32_t BAR_B1F = OFF_BAR, BAR_B1E = OFF_BAR + 32, BAR_KVF = OFF_BAR + 64, BAR_KVE = OFF_BAR + 104,
                   BAR_AF = OFF_BAR + 144, BAR_AE = OFF_BAR + 168, BAR_OBF = OFF_BAR + 192, BAR_WOB = OFF_BAR + 248,
                   BAR_ADONE = OFF_BAR + 256, BAR_B1D = OFF_BAR + 264;
constexpr uint32_t OFF_EPOCH = OFF_BAR + 272;
constexpr uint32_t OFF_KN    = OFF_BAR + 288;
constexpr uint32_t OFF_QN    = OFF_BAR + 352;
constexpr uint32_t OFF_KMAX  = OFF_BAR + 416;
constexpr uint32_t SMEM_BYTES = OFF_BAR + 1024;

constexpr float SAFE_BOUND_SQ = 40.f * 40.f * 0.97f;
constexpr float Q_SCALE = 0.18898223650461362f * 1.4426950408889634f;

__device__ uint4 g_kv[8 * 16 * 2 * (KV_SLOT / 16)];
__device__ __nv_bfloat16 g_o[2 * SEQ * DM];
__device__ float4 g_akv[8 * 16 * 4 * 128];
__device__ unsigned long long g_kvflag[8 * 16];
__device__ unsigned int g_akvflag[8];
__device__ unsigned int g_aoflag[16];
__device__ unsigned int g_boflag[32];
__device__ unsigned long long g_done;
#define TRACE(i) do {} while (0)

#define DESC_HI 0x40000040

%0, %1, %2, %3, %4, %5, %6, %7, %8, %9, %10, %11, %12, %13, %14, %15

__device__ __forceinline__ void wg_fence() { asm volatile("wgmma.fence.sync.aligned;" ::: "memory"); }
__device__ __forceinline__ void wg_commit() { asm volatile("wgmma.commit_group.sync.aligned;" ::: "memory"); }
template <int N> __device__ __forceinline__ void wg_wait() { asm volatile("wgmma.wait_group.sync.aligned %0;" ::"n"(N) : "memory"); }
template <int N> __device__ __forceinline__ void pin(float (&d)[N]) {
#pragma unroll
    for (int i = 0; i < N; i++) asm volatile("" : "+f"(d[i])::"memory");
}
template <int N> __device__ __forceinline__ void pin(uint32_t (&d)[N]) {
#pragma unroll
    for (int i = 0; i < N; i++) asm volatile("" : "+r"(d[i])::"memory");
}
__device__ __forceinline__ uint32_t dlo(uint32_t addr, uint32_t lbo = 0) { return ((addr >> 4) & 0x3FFF) | ((lbo >> 4) << 16); }
__device__ __forceinline__ float ex2(float x) { float y; asm("ex2.approx.ftz.f32 %0, %1;" : "=f"(y) : "f"(x)); return y; }
__device__ __forceinline__ uint32_t pack(float lo, float hi) { uint32_t r; asm("cvt.rn.bf16x2.f32 %0, %1, %2;" : "=r"(r) : "f"(hi), "f"(lo)); return r; }
__device__ __forceinline__ float rbf(float x) { return __bfloat162float(__float2bfloat16_rn(x)); }
__device__ __forceinline__ float bf_lo(uint32_t v) { return __uint_as_float(v << 16); }
__device__ __forceinline__ float bf_hi(uint32_t v) { return __uint_as_float(v & 0xFFFF0000u); }

__device__ __forceinline__ void mbar_init(uint32_t bar, uint32_t cnt) { asm volatile("mbarrier.init.shared::cta.b64 [%0], %1;" ::"r"(bar), "r"(cnt)); }
__device__ __forceinline__ void mbar_expect(uint32_t bar, uint32_t bytes) { asm volatile("mbarrier.arrive.expect_tx.shared::cta.b64 _, [%0], %1;" ::"r"(bar), "r"(bytes) : "memory"); }
__device__ __forceinline__ void mbar_arrive(uint32_t bar) { asm volatile("mbarrier.arrive.shared::cta.b64 _, [%0];" ::"r"(bar) : "memory"); }
__device__ __forceinline__ void mbar_wait(uint32_t bar, uint32_t parity) {
    asm volatile(
        "{\n.reg .pred p;\n.reg .u32 c;\nmov.u32 c, 0;\n"
        "W_LOOP:\nmbarrier.try_wait.parity.shared::cta.b64 p, [%0], %1;\n@p bra W_DONE;\n"
        "add.u32 c, c, 1;\nsetp.lt.u32 p, c, 0x1000000;\n@p bra W_LOOP;\ntrap;\nW_DONE:\n}\n" ::"r"(bar), "r"(parity) : "memory");
}
__device__ __forceinline__ void warp_arrive(uint32_t bar) { if ((threadIdx.x & 31) == 0) mbar_arrive(bar); }
__device__ __forceinline__ void named_sync(int id) { asm volatile("bar.sync %0, 128;" ::"r"(id) : "memory"); }
__device__ __forceinline__ void fence_async() { asm volatile("fence.proxy.async;" ::: "memory"); }
__device__ __forceinline__ void fence_async_smem() { asm volatile("fence.proxy.async.shared::cta;" ::: "memory"); }

__device__ __forceinline__ void tma_load(uint32_t dst, const CUtensorMap* m, int c0, int c1, uint32_t bar) {
    asm volatile("cp.async.bulk.tensor.2d.shared::cluster.global.mbarrier::complete_tx::bytes [%0], [%1, {%3, %4}], [%2];"
                 ::"r"(dst), "l"(m), "r"(bar), "r"(c0), "r"(c1) : "memory");
}
__device__ __forceinline__ void tma_store(const CUtensorMap* m, int c0, int c1, uint32_t src) {
    asm volatile("cp.async.bulk.tensor.2d.global.shared::cta.bulk_group [%0, {%2, %3}], [%1];" ::"l"(m), "r"(src), "r"(c0), "r"(c1) : "memory");
}
__device__ __forceinline__ void bulk_load(uint32_t dst, const void* src, uint32_t bytes, uint32_t bar) {
    asm volatile("cp.async.bulk.shared::cluster.global.mbarrier::complete_tx::bytes [%0], [%1], %2, [%3];" ::"r"(dst), "l"(src), "r"(bytes), "r"(bar) : "memory");
}
__device__ __forceinline__ void bulk_store(void* dst, uint32_t src, uint32_t bytes) {
    asm volatile("cp.async.bulk.global.shared::cta.bulk_group [%0], [%1], %2;" ::"l"(dst), "r"(src), "r"(bytes) : "memory");
}
__device__ __forceinline__ void bulk_commit() { asm volatile("cp.async.bulk.commit_group;" ::: "memory"); }
__device__ __forceinline__ void bulk_wait_all() { asm volatile("cp.async.bulk.wait_group 0;" ::: "memory"); }
__device__ __forceinline__ void bulk_wait_read() { asm volatile("cp.async.bulk.wait_group.read 0;" ::: "memory"); }

__device__ __forceinline__ void red_release(unsigned int* p) { asm volatile("red.release.gpu.global.add.u32 [%0], 1;" ::"l"(p) : "memory"); }
__device__ __forceinline__ void wait_count(const unsigned int* p, uint32_t target) {
    for (uint32_t n = 0;; n++) {
        uint32_t v;
        asm volatile("ld.acquire.gpu.global.u32 %0, [%1];" : "=r"(v) : "l"(p) : "memory");
        if ((int32_t)(v - target) >= 0) break;
        if (n > (1u << 22)) __trap();
    }
}
__device__ __forceinline__ void stsm4(uint32_t addr, uint32_t a, uint32_t b, uint32_t c, uint32_t d) {
    asm volatile("stmatrix.sync.aligned.m8n8.x4.shared.b16 [%0], {%1, %2, %3, %4};" ::"r"(addr), "r"(a), "r"(b), "r"(c), "r"(d) : "memory");
}
__device__ __forceinline__ void stsm2(uint32_t addr, uint32_t a, uint32_t b) {
    asm volatile("stmatrix.sync.aligned.m8n8.x2.shared.b16 [%0], {%1, %2};" ::"r"(addr), "r"(a), "r"(b) : "memory");
}
__device__ __forceinline__ float lds_f(uint32_t addr) { float v; asm volatile("ld.shared.f32 %0, [%1];" : "=f"(v) : "r"(addr) : "memory"); return v; }
__device__ __forceinline__ void sts_f(uint32_t addr, float v) { asm volatile("st.shared.f32 [%0], %1;" ::"r"(addr), "f"(v) : "memory"); }
__device__ __forceinline__ uint32_t lds_u(uint32_t addr) { uint32_t v; asm volatile("ld.shared.u32 %0, [%1];" : "=r"(v) : "r"(addr) : "memory"); return v; }
__device__ __forceinline__ float umaxf(float a, float b) { return __uint_as_float(max(__float_as_uint(a), __float_as_uint(b))); }

__device__ __forceinline__ void store_tile16(uint32_t tile, int row0, const uint32_t (&v)[16]) {
    const int lane = threadIdx.x & 31;
    const int row = row0 + (lane & 7) + ((lane >> 3) & 1) * 8;
    const uint32_t base = tile + row * 128;
#pragma unroll
    for (int c = 0; c < 8; c += 2) stsm4(base + (((c + (lane >> 4)) ^ (lane & 7)) << 4), v[2 * c], v[2 * c + 1], v[2 * c + 2], v[2 * c + 3]);
}
__device__ __forceinline__ void spread_pair(const uint32_t (&p)[14], uint32_t (&v)[16], uint32_t pad_lo, uint32_t pad_hi) {
    const bool lo = (threadIdx.x & 2) == 0;
#pragma unroll
    for (int i = 0; i < 6; i++) { v[i] = p[i]; v[10 + i] = p[8 + i]; }
    v[6] = lo ? p[6] : pad_lo; v[7] = lo ? p[7] : pad_lo;
    v[8] = lo ? pad_hi : p[6]; v[9] = lo ? pad_hi : p[7];
}
__device__ __forceinline__ void pair_norms(const float* a, float& n0, float& n1, bool poison) {
    const bool lo = (threadIdx.x & 2) == 0;
    float s00 = 0.f, s01 = 0.f, s10 = 0.f, s11 = 0.f;
#pragma unroll
    for (int j = 0; j < 3; j++) {
        s00 = fmaf(a[4 * j], a[4 * j], fmaf(a[4 * j + 1], a[4 * j + 1], s00));
        s10 = fmaf(a[4 * j + 2], a[4 * j + 2], fmaf(a[4 * j + 3], a[4 * j + 3], s10));
        s01 = fmaf(a[16 + 4 * j], a[16 + 4 * j], fmaf(a[17 + 4 * j], a[17 + 4 * j], s01));
        s11 = fmaf(a[18 + 4 * j], a[18 + 4 * j], fmaf(a[19 + 4 * j], a[19 + 4 * j], s11));
    }
    const float t0 = fmaf(a[12], a[12], a[13] * a[13]), t1 = fmaf(a[14], a[14], a[15] * a[15]);
    if (lo) { s00 += t0; s10 += t1; } else { s01 += t0; s11 += t1; }
    if (poison) { s00 = __int_as_float(0x7f800000); s01 = s00; }
#pragma unroll
    for (int m = 1; m <= 2; m <<= 1) {
        s00 += __shfl_xor_sync(0xffffffffu, s00, m); s01 += __shfl_xor_sync(0xffffffffu, s01, m);
        s10 += __shfl_xor_sync(0xffffffffu, s10, m); s11 += __shfl_xor_sync(0xffffffffu, s11, m);
    }
    n0 = __uint_as_float(__reduce_max_sync(0xffffffffu, max(__float_as_uint(s00), __float_as_uint(s10))));
    n1 = __uint_as_float(__reduce_max_sync(0xffffffffu, max(__float_as_uint(s01), __float_as_uint(s11))));
}

__device__ __forceinline__ void qk(float (&S)[32], const uint32_t (&Q)[8], uint32_t klo) {
    mma_rs_n64_k(S, Q[0], Q[1], Q[2], Q[3], klo, 0);
    mma_rs_n64_k(S, Q[4], Q[5], Q[6], Q[7], klo + 2, 1);
}
__device__ __forceinline__ void pv(float (&O)[16], const uint32_t (&P)[16], uint32_t vlo) {
#pragma unroll
    for (int s = 0; s < 4; s++) mma_rs_n32_n(O, P[4 * s], P[4 * s + 1], P[4 * s + 2], P[4 * s + 3], vlo + s * 128, 1);
}
template <bool SAFE>
__device__ __forceinline__ void softmax_tile(float (&S)[32], uint32_t (&P)[16], float (&O)[16], float (&m)[2]) {
    if (SAFE) {
#pragma unroll
        for (int j = 0; j < 16; j++) P[j] = pack(ex2(S[2 * j]), ex2(S[2 * j + 1]));
    } else {
        float m0 = m[0], m1 = m[1];
#pragma unroll
        for (int j = 0; j < 8; j++) { m0 = fmaxf(m0, fmaxf(S[4 * j], S[4 * j + 1])); m1 = fmaxf(m1, fmaxf(S[4 * j + 2], S[4 * j + 3])); }
        m0 = fmaxf(m0, __shfl_xor_sync(0xffffffffu, m0, 1)); m1 = fmaxf(m1, __shfl_xor_sync(0xffffffffu, m1, 1));
        m0 = fmaxf(m0, __shfl_xor_sync(0xffffffffu, m0, 2)); m1 = fmaxf(m1, __shfl_xor_sync(0xffffffffu, m1, 2));
        const float s0 = ex2(m[0] - m0), s1 = ex2(m[1] - m1);
        m[0] = m0; m[1] = m1;
#pragma unroll
        for (int j = 0; j < 4; j++) { O[4 * j] *= s0; O[4 * j + 1] *= s0; O[4 * j + 2] *= s1; O[4 * j + 3] *= s1; }
#pragma unroll
        for (int j = 0; j < 8; j++) {
            P[2 * j] = pack(ex2(S[4 * j] - m0), ex2(S[4 * j + 1] - m0));
            P[2 * j + 1] = pack(ex2(S[4 * j + 2] - m1), ex2(S[4 * j + 3] - m1));
        }
    }
}

struct Att {
    float S0[32], S1[32], O0[16], O1[16], m0[2], m1[2];
    uint32_t P0[16], P1[16], Q0[8], Q1[8];
    float qn0, qn1;
    uint32_t sb, kb;
    int slot, pslot; uint32_t par;
    bool safe;

    __device__ __forceinline__ void check(int t) {
        const float k0 = lds_f(sb + OFF_KMAX + t * 8), k1 = lds_f(sb + OFF_KMAX + t * 8 + 4);
        safe = (qn0 * k0 <= SAFE_BOUND_SQ) && (qn1 * k1 <= SAFE_BOUND_SQ);
    }
    template <bool SAFE>
    __device__ __forceinline__ void step(int t) {
        int nslot = slot + 1; uint32_t npar = par;
        if (nslot == KV_SLOTS) { nslot = 0; npar ^= 1; }
        const bool last = (t == 31);
        const uint32_t kc = kb + slot * 1024, vp = kb + pslot * 1024 + 512;
        const uint32_t kn = last ? kc : kb + nslot * 1024;
        wg_fence(); pv(O1, P1, vp + 4); qk(S1, Q1, kc + 4); wg_commit();
        softmax_tile<SAFE>(S0, P0, O0, m0);
        pin(P0); pin(O0);
        mbar_wait(sb + BAR_KVF + (last ? slot : nslot) * 8, last ? par : npar);
        if (SAFE) check(last ? t : t + 1);
        wg_fence(); pv(O0, P0, kc + 512); qk(S0, Q0, kn); wg_commit();
        wg_wait<1>(); pin(S1); pin(O1);
        if (t > 0) warp_arrive(sb + BAR_KVE + pslot * 8);
        softmax_tile<SAFE>(S1, P1, O1, m1);
        pin(P1); pin(O1);
        wg_wait<0>(); pin(S0); pin(O0);
        pslot = slot; slot = nslot; par = npar;
    }
};

__device__ __forceinline__ float phi(float acc) {
    const float t = rbf(acc);
    const float e = ex2(t * 1.4426950408889634f);
    return rbf(t > 0.f ? t + 1.f : e) + 1e-6f;
}

__device__ __forceinline__ void store_out(const float (&acc)[56], uint32_t stage, const CUtensorMap* map, int col, int row) {
    const int lane = threadIdx.x & 31, w = (threadIdx.x >> 5) & 3;
    const uint32_t base = stage + (w * 16 + (lane & 7) + ((lane >> 3) & 1) * 8) * 224 + (lane >> 4) * 16;
#pragma unroll
    for (int c = 0; c < 14; c += 2)
        stsm4(base + c * 16, pack(acc[4 * c], acc[4 * c + 1]), pack(acc[4 * c + 2], acc[4 * c + 3]),
              pack(acc[4 * c + 4], acc[4 * c + 5]), pack(acc[4 * c + 6], acc[4 * c + 7]));
    fence_async_smem();
    named_sync(3);
    if ((threadIdx.x & 127) == 0) { tma_store(map, col, row, stage); bulk_commit(); bulk_wait_read(); }
}
__device__ __forceinline__ void store_pair112(uint32_t stage, int row0, const uint32_t (&p)[14]) {
    const int lane = threadIdx.x & 31;
    const uint32_t base = stage + (row0 + (lane & 7) + ((lane >> 3) & 1) * 8) * 112;
    const uint32_t b4 = base + (lane >> 4) * 16;
    stsm4(b4, p[0], p[1], p[2], p[3]);
    stsm4(b4 + 32, p[4], p[5], p[6], p[7]);
    stsm4(b4 + 64, p[8], p[9], p[10], p[11]);
    stsm2(base + 96, p[12], p[13]);
}

struct Maps { CUtensorMap xA, wA, woA, xB, wB, woB, oLd, oSt, out; };

__global__ void __launch_bounds__(512, 1) fused_kernel(const __grid_constant__ Maps maps) {
    extern __shared__ __align__(1024) uint8_t smem_raw[];
    const uint32_t sb = (uint32_t)__cvta_generic_to_shared(smem_raw);
    const int tid = threadIdx.x;
    const int wg = __shfl_sync(0xffffffffu, tid >> 7, 0);
    const int r = blockIdx.x >> 3, hp = blockIdx.x & 7;
    const int half = hp >> 2, cq = hp & 3;

    auto b1_issue = [&](int kb) {
        const uint32_t st = sb + OFF_B1 + (kb & 3) * B1_STAGE, bar = sb + BAR_B1F + (kb & 3) * 8;
        mbar_expect(bar, B1_STAGE);
        tma_load(st, &maps.xB, kb * 64, r * 128, bar);
#pragma unroll
        for (int p = 0; p < 3; p++) tma_load(st + 16384 + p * 8192, &maps.wB, p * DM + hp * 56, kb * 64, bar);
    };

    unsigned long long done0 = 0;
    if (tid == 384) {
        TRACE(0);
        if (sb & 1023) __trap();
#pragma unroll
        for (int i = 0; i < 4; i++) { mbar_init(sb + BAR_B1F + i * 8, 1); mbar_init(sb + BAR_B1E + i * 8, 8); }
#pragma unroll
        for (int i = 0; i < KV_SLOTS; i++) { mbar_init(sb + BAR_KVF + i * 8, 1); mbar_init(sb + BAR_KVE + i * 8, 8); }
#pragma unroll
        for (int i = 0; i < 3; i++) { mbar_init(sb + BAR_AF + i * 8, 1); mbar_init(sb + BAR_AE + i * 8, 4); }
#pragma unroll
        for (int i = 0; i < 7; i++) mbar_init(sb + BAR_OBF + i * 8, 1);
        mbar_init(sb + BAR_WOB, 1); mbar_init(sb + BAR_ADONE, 1); mbar_init(sb + BAR_B1D, 8);
        asm volatile("fence.mbarrier_init.release.cluster;" ::: "memory");
        fence_async();
#pragma unroll
        for (int kb = 0; kb < 4; kb++) b1_issue(kb);
        asm volatile("ld.relaxed.gpu.global.u64 %0, [%1];" : "=l"(done0) : "l"(&g_done) : "memory");
        TRACE(1);
    }
    __syncthreads();

    if (wg < 2) {
        asm volatile("setmaxnreg.inc.sync.aligned.u32 176;");
        const int lane = tid & 31, w = (tid >> 5) & 3;
        Att a;
        a.sb = sb; a.kb = dlo(sb + OFF_KV);
        {
            float acc[92];
#pragma unroll 1
            for (int kb = 0; kb < 7; kb++) {
                const uint32_t st = sb + OFF_B1 + (kb & 3) * B1_STAGE;
                mbar_wait(sb + BAR_B1F + (kb & 3) * 8, kb >> 2);
                const uint32_t da = dlo(st + wg * 8192), db = dlo(st + 16384, 8192);
                wg_fence();
#pragma unroll
                for (int ks = 0; ks < 4; ks++) mma_ss_n184_kn(acc, da + ks * 2, db + ks * 128, (kb | ks) != 0);
                wg_commit();
                if (kb > 0) { wg_wait<1>(); if (kb < 4) warp_arrive(sb + BAR_B1E + (kb - 1) * 8); }
            }
            wg_wait<0>(); pin(acc);
            warp_arrive(sb + BAR_B1D);
            if (tid == 0) TRACE(2);
            uint32_t p[14], v[16];
#pragma unroll
            for (int i = 0; i < 14; i++) p[i] = pack(acc[32 + 2 * i], acc[33 + 2 * i]);
            spread_pair(p, v, 0u, 0u);
            store_tile16(sb + OFF_KV + wg * KV_SLOT, w * 16, v);
            float vmax = 0.f;
#pragma unroll
            for (int i = 0; i < 28; i++) vmax = umaxf(vmax, fabsf(acc[64 + i]));
#pragma unroll
            for (int i = 0; i < 14; i++) p[i] = pack(acc[64 + 2 * i], acc[65 + 2 * i]);
            spread_pair(p, v, (lane & 3) == 2 ? 0x3F80u : 0u, (lane & 3) == 0 ? 0x3F80u : 0u);
            store_tile16(sb + OFF_KV + wg * KV_SLOT + 8192, w * 16, v);
            float kn0, kn1;
            pair_norms(acc + 32, kn0, kn1, !(vmax <= 1e18f));
#pragma unroll
            for (int i = 0; i < 28; i++) acc[i] *= Q_SCALE;
#pragma unroll
            for (int i = 0; i < 14; i++) p[i] = pack(acc[2 * i], acc[2 * i + 1]);
            spread_pair(p, v, 0u, 0u);
#pragma unroll
            for (int i = 0; i < 8; i++) { a.Q0[i] = v[i]; a.Q1[i] = v[8 + i]; }
            float qn0, qn1;
            pair_norms(acc, qn0, qn1, false);
            if (lane == 0) {
                const uint32_t o = (wg * 4 + w) * 8;
                sts_f(sb + OFF_KN + o, kn0); sts_f(sb + OFF_KN + o + 4, kn1);
                sts_f(sb + OFF_QN + o, qn0); sts_f(sb + OFF_QN + o + 4, qn1);
            }
            fence_async_smem();
            named_sync(1 + wg);
            const uint32_t qb = sb + OFF_QN + wg * 32;
            a.qn0 = umaxf(umaxf(lds_f(qb), lds_f(qb + 8)), umaxf(lds_f(qb + 16), lds_f(qb + 24)));
            a.qn1 = umaxf(umaxf(lds_f(qb + 4), lds_f(qb + 12)), umaxf(lds_f(qb + 20), lds_f(qb + 28)));
            if ((tid & 127) == 0) {
                const uint32_t kq = sb + OFF_KN + wg * 32;
                sts_f(sb + OFF_KMAX + wg * 8, umaxf(umaxf(lds_f(kq), lds_f(kq + 8)), umaxf(lds_f(kq + 16), lds_f(kq + 24))));
                sts_f(sb + OFF_KMAX + wg * 8 + 4, umaxf(umaxf(lds_f(kq + 4), lds_f(kq + 12)), umaxf(lds_f(kq + 20), lds_f(kq + 28))));
                mbar_arrive(sb + BAR_KVF + wg * 8);
            }
        }
#pragma unroll
        for (int i = 0; i < 16; i++) { a.O0[i] = 0.f; a.O1[i] = 0.f; a.P1[i] = 0u; }
        pin(a.O0); pin(a.O1); pin(a.P1); pin(a.Q0); pin(a.Q1);
        a.slot = 0; a.pslot = 0; a.par = 0;
        mbar_wait(sb + BAR_KVF, 0);
        if (tid == 0) TRACE(3);
        a.check(0);
        wg_fence(); qk(a.S0, a.Q0, a.kb); wg_commit(); wg_wait<0>(); pin(a.S0);
        int t = 0;
#pragma unroll 1
        for (; t < 32 && a.safe; t++) {
            a.step<true>(t);
        }
        if (t < 32) {
            const float m_init = t > 0 ? 0.f : __int_as_float(0xff800000);
            a.m0[0] = a.m0[1] = a.m1[0] = a.m1[1] = m_init;
#pragma unroll 1
            for (; t < 32; t++) a.step<false>(t);
        }
        wg_fence(); pv(a.O1, a.P1, a.kb + a.pslot * 1024 + 512 + 4); wg_commit(); wg_wait<0>(); pin(a.O1);
        warp_arrive(sb + BAR_KVE + a.pslot * 8);
        if (tid == 0) TRACE(8);
        {
            const int q0 = lane & ~3;
            const float i00 = 1.f / __shfl_sync(0xffffffffu, a.O0[12], q0 | 2), i01 = 1.f / __shfl_sync(0xffffffffu, a.O0[14], q0 | 2);
            const float i10 = 1.f / __shfl_sync(0xffffffffu, a.O1[0], q0), i11 = 1.f / __shfl_sync(0xffffffffu, a.O1[2], q0);
            uint32_t p[14];
#pragma unroll
            for (int j = 0; j < 3; j++) {
                p[2 * j] = pack(a.O0[4 * j] * i00, a.O0[4 * j + 1] * i00);
                p[2 * j + 1] = pack(a.O0[4 * j + 2] * i01, a.O0[4 * j + 3] * i01);
                p[8 + 2 * j] = pack(a.O1[4 * j + 4] * i10, a.O1[4 * j + 5] * i10);
                p[9 + 2 * j] = pack(a.O1[4 * j + 6] * i11, a.O1[4 * j + 7] * i11);
            }
            const bool lo = (lane & 2) == 0;
            p[6] = lo ? pack(a.O0[12] * i00, a.O0[13] * i00) : pack(a.O1[0] * i10, a.O1[1] * i10);
            p[7] = lo ? pack(a.O0[14] * i01, a.O0[15] * i01) : pack(a.O1[2] * i11, a.O1[3] * i11);
            const uint32_t stage = sb + OFF_MISC + wg * 8192;
            store_pair112(stage, w * 16, p);
            fence_async_smem();
            named_sync(1 + wg);
            if ((tid & 127) == 0) {
                tma_store(&maps.oSt, hp * 56, SEQ + r * 128 + wg * 64, stage);
                bulk_commit(); bulk_wait_all();
                fence_async();
                red_release(&g_boflag[r * 2 + wg]);
                if (tid == 0) TRACE(9);
            }
        }
    } else if (wg == 2) {
        asm volatile("setmaxnreg.dec.sync.aligned.u32 120;");
        const int lane = tid & 31, w = (tid >> 5) & 3, t128 = tid & 127;
        int st = 0; uint32_t par = 0;
#pragma unroll 1
        for (int part = 0; part < 3; part++) {
            float acc0[28], acc1[28];
#pragma unroll 1
            for (int kb = 0; kb < 7; kb++) {
                const uint32_t base = sb + OFF_A + st * A_STAGE;
                mbar_wait(sb + BAR_AF + st * 8, par);
                const uint32_t da = dlo(base), db = dlo(base + 16384);
                wg_fence();
#pragma unroll
                for (int ks = 0; ks < 4; ks++) {
                    mma_ss_n56_kn(acc0, da + ks * 2, db + ks * 128, (kb | ks) != 0);
                    mma_ss_n56_kn(acc1, da + 512 + ks * 2, db + ks * 128, (kb | ks) != 0);
                }
                wg_commit(); wg_wait<0>();
                warp_arrive(sb + BAR_AE + st * 8);
                if (++st == 3) { st = 0; par ^= 1; }
            }
            pin(acc0); pin(acc1);
            const bool is_v = (part == 1);
            const uint32_t tile = sb + (part == 0 ? OFF_PK : is_v ? OFF_AV : OFF_PQ);
            const uint32_t pad_lo = (is_v && (lane & 3) == 2) ? 0x3F80u : 0u, pad_hi = (is_v && (lane & 3) == 0) ? 0x3F80u : 0u;
            if (!is_v) {
#pragma unroll
                for (int i = 0; i < 28; i++) { acc0[i] = phi(acc0[i]); acc1[i] = phi(acc1[i]); }
            }
            uint32_t p[14], v[16];
#pragma unroll
            for (int i = 0; i < 14; i++) p[i] = pack(acc0[2 * i], acc0[2 * i + 1]);
            spread_pair(p, v, pad_lo, pad_hi);
            store_tile16(tile, w * 16, v);
#pragma unroll
            for (int i = 0; i < 14; i++) p[i] = pack(acc1[2 * i], acc1[2 * i + 1]);
            spread_pair(p, v, pad_lo, pad_hi);
            store_tile16(tile, 64 + w * 16, v);
            if (is_v) {
                fence_async_smem();
                named_sync(3);
                float d[32];
                const uint32_t da = dlo(sb + OFF_PK), db = dlo(sb + OFF_AV);
                wg_fence();
#pragma unroll
                for (int ks = 0; ks < 8; ks++) mma_ss_n64_mn(d, da + ks * 128, db + ks * 128, ks != 0);
                wg_commit(); wg_wait<0>(); pin(d);
                float4* dst = g_akv + (hp * 16 + r) * 512 + t128;
#pragma unroll
                for (int i = 0; i < 4; i++)
                    dst[i * 128] = w < 2 ? make_float4(d[4 * i], d[4 * i + 1], d[4 * i + 2], d[4 * i + 3])
                                         : make_float4(d[16 + 4 * i], d[17 + 4 * i], d[18 + 4 * i], d[19 + 4 * i]);
                named_sync(3);
                if (t128 == 0) { __threadfence(); red_release(&g_akvflag[hp]); TRACE(16); }
            }
        }
        const uint32_t e1 = lds_u(sb + OFF_EPOCH);
        if (t128 == 0) { TRACE(17); wait_count(&g_akvflag[hp], e1 * 16); }
        named_sync(3);
        {
            float s[16];
#pragma unroll
            for (int i = 0; i < 16; i++) s[i] = 0.f;
            const float4* src = g_akv + hp * 16 * 512 + t128;
#pragma unroll 2
            for (int rr = 0; rr < 16; rr++) {
#pragma unroll
                for (int i = 0; i < 4; i++) {
                    const float4 x = __ldcg(src + rr * 512 + i * 128);
                    s[4 * i] += x.x; s[4 * i + 1] += x.y; s[4 * i + 2] += x.z; s[4 * i + 3] += x.w;
                }
            }
            uint32_t v[16];
#pragma unroll
            for (int i = 0; i < 8; i++) {
                const uint32_t x = pack(s[2 * i], s[2 * i + 1]);
                v[i] = w < 2 ? x : 0u; v[8 + i] = w < 2 ? 0u : x;
            }
            store_tile16(sb + OFF_KVB, w * 16, v);
        }
        fence_async_smem();
        named_sync(3);
        {
            float n0[32], n1[32];
            const uint32_t da = dlo(sb + OFF_PQ), db = dlo(sb + OFF_KVB);
            wg_fence();
#pragma unroll
            for (int ks = 0; ks < 4; ks++) {
                mma_ss_n64_kn(n0, da + ks * 2, db + ks * 128, ks != 0);
                mma_ss_n64_kn(n1, da + 512 + ks * 2, db + ks * 128, ks != 0);
            }
            wg_commit(); wg_wait<0>(); pin(n0); pin(n1);
            const int q0 = lane & ~3;
            const bool lo = (lane & 2) == 0;
            auto finish = [&](const float (&n)[32], int row0) {
                const float i00 = 1.f / rbf(rbf(__shfl_sync(0xffffffffu, n[12], q0 | 2)) + 1e-6f);
                const float i01 = 1.f / rbf(rbf(__shfl_sync(0xffffffffu, n[14], q0 | 2)) + 1e-6f);
                const float i10 = 1.f / rbf(rbf(__shfl_sync(0xffffffffu, n[16], q0)) + 1e-6f);
                const float i11 = 1.f / rbf(rbf(__shfl_sync(0xffffffffu, n[18], q0)) + 1e-6f);
                uint32_t p[14];
#pragma unroll
                for (int j = 0; j < 3; j++) {
                    p[2 * j] = pack(rbf(n[4 * j]) * i00, rbf(n[4 * j + 1]) * i00);
                    p[2 * j + 1] = pack(rbf(n[4 * j + 2]) * i01, rbf(n[4 * j + 3]) * i01);
                    p[8 + 2 * j] = pack(rbf(n[20 + 4 * j]) * i10, rbf(n[21 + 4 * j]) * i10);
                    p[9 + 2 * j] = pack(rbf(n[22 + 4 * j]) * i11, rbf(n[23 + 4 * j]) * i11);
                }
                p[6] = lo ? pack(rbf(n[12]) * i00, rbf(n[13]) * i00) : pack(rbf(n[16]) * i10, rbf(n[17]) * i10);
                p[7] = lo ? pack(rbf(n[14]) * i01, rbf(n[15]) * i01) : pack(rbf(n[18]) * i11, rbf(n[19]) * i11);
                store_pair112(sb + OFF_PK, row0, p);
            };
            finish(n0, w * 16);
            finish(n1, 64 + w * 16);
            fence_async_smem();
            named_sync(3);
            if (t128 == 0) {
                tma_store(&maps.oSt, hp * 56, r * 128, sb + OFF_PK);
                tma_store(&maps.oSt, hp * 56, r * 128 + 64, sb + OFF_PK + 64 * 112);
                bulk_commit(); bulk_wait_all();
                fence_async();
                red_release(&g_aoflag[r]);
                TRACE(18);
            }
        }
        {
            float acc[56];
#pragma unroll 1
            for (int kb = 0; kb < 7; kb++) {
                const uint32_t base = sb + OFF_A + st * A_STAGE;
                mbar_wait(sb + BAR_AF + st * 8, par);
                const uint32_t da = dlo(base), db = dlo(base + 8192, 8192);
                wg_fence();
#pragma unroll
                for (int ks = 0; ks < 4; ks++) mma_ss_n112_kn(acc, da + ks * 2, db + ks * 128, (kb | ks) != 0);
                wg_commit(); wg_wait<0>();
                if (++st == 3) { st = 0; par ^= 1; }
                if (kb < 4) warp_arrive(sb + BAR_AE + (st == 0 ? 2 : st - 1) * 8);
            }
            pin(acc);
            store_out(acc, sb + OFF_AV, &maps.out, cq * 112, r * 128 + half * 64);
            if (t128 == 0) { mbar_arrive(sb + BAR_ADONE); TRACE(19); }
        }
        {
            float acc[56];
            mbar_wait(sb + BAR_WOB, 0);
#pragma unroll 1
            for (int kb = 0; kb < 7; kb++) {
                mbar_wait(sb + BAR_OBF + kb * 8, 0);
                if (t128 == 0 && kb == 0) TRACE(20);
                const uint32_t da = dlo(sb + OFF_KV + kb * 8192), db = dlo(sb + OFF_A + kb * 16384, 8192);
                wg_fence();
#pragma unroll
                for (int ks = 0; ks < 4; ks++) mma_ss_n112_kn(acc, da + ks * 2, db + ks * 128, (kb | ks) != 0);
                wg_commit();
            }
            wg_wait<0>(); pin(acc);
            if (t128 == 0) TRACE(21);
            store_out(acc, sb + OFF_OUTB, &maps.out, DM + cq * 112, r * 128 + half * 64);
            if (t128 == 0) { atomicAdd(&g_done, 1ull); TRACE(22); }
        }
    } else {
        asm volatile("setmaxnreg.dec.sync.aligned.u32 40;");
        if (tid == 384) {
            const uint32_t e1 = (uint32_t)(done0 / NCTA) + 1;
#pragma unroll 1
            for (int kb = 4; kb < 7; kb++) {
                mbar_wait(sb + BAR_B1E + (kb & 3) * 8, 0);
                if (kb == 6) asm volatile("st.shared.u32 [%0], %1;" ::"r"(sb + OFF_EPOCH), "r"(e1) : "memory");
                b1_issue(kb);
            }
            const uint8_t* kvg = reinterpret_cast<const uint8_t*>(g_kv) + (size_t)hp * 16 * 2 * KV_SLOT;
            mbar_wait(sb + BAR_KVF, 0);
            bulk_store(const_cast<uint8_t*>(kvg) + (size_t)r * 2 * KV_SLOT, sb + OFF_KV, KV_SLOT);
            mbar_wait(sb + BAR_KVF + 8, 0);
            bulk_store(const_cast<uint8_t*>(kvg) + (size_t)(r * 2 + 1) * KV_SLOT, sb + OFF_KV + KV_SLOT, KV_SLOT);
            bulk_commit();
            {
                const float k0 = umaxf(lds_f(sb + OFF_KMAX), lds_f(sb + OFF_KMAX + 8));
                const float k1 = umaxf(lds_f(sb + OFF_KMAX + 4), lds_f(sb + OFF_KMAX + 12));
                const uint32_t nb = (min(__float_as_uint(k0) + 0xFFFFu, 0x7FFFFFFFu) >> 16) | (min(__float_as_uint(k1) + 0xFFFFu, 0x7FFFFFFFu) & 0xFFFF0000u);
                const unsigned long long val = ((unsigned long long)e1 << 32) | nb;
                bulk_wait_all();
                fence_async();
                asm volatile("st.release.gpu.global.u64 [%0], %1;" ::"l"(&g_kvflag[hp * 16 + r]), "l"(val) : "memory");
            }
            TRACE(10);
            int slot = 2; uint32_t epar = 1;
            uint32_t nb = 0;
#pragma unroll 1
            for (int t = 2; t < 32; t++) {
                const int i = (t >> 1) - 1, blk = i + (i >= r ? 1 : 0);
                if ((t & 1) == 0) {
                    unsigned long long v;
                    for (uint32_t n = 0;; n++) {
                        asm volatile("ld.acquire.gpu.global.u64 %0, [%1];" : "=l"(v) : "l"(&g_kvflag[hp * 16 + blk]) : "memory");
                        if ((uint32_t)(v >> 32) == e1) break;
                        if (n > (1u << 22)) __trap();
                    }
                    nb = (uint32_t)v;
                    fence_async();
                }
                if (t == 4) mbar_wait(sb + BAR_B1D, 0);
                mbar_wait(sb + BAR_KVE + slot * 8, epar);
                sts_f(sb + OFF_KMAX + t * 8, bf_lo(nb)); sts_f(sb + OFF_KMAX + t * 8 + 4, bf_hi(nb));
                mbar_expect(sb + BAR_KVF + slot * 8, KV_SLOT);
                bulk_load(sb + OFF_KV + slot * KV_SLOT, kvg + (size_t)(blk * 2 + (t & 1)) * KV_SLOT, KV_SLOT, sb + BAR_KVF + slot * 8);
                if (t == 2 || t == 3) TRACE(9 + t);
                if (++slot == KV_SLOTS) { slot = 0; epar ^= 1; }
            }
            mbar_wait(sb + BAR_KVE + 2 * 8, 1); mbar_wait(sb + BAR_KVE + 3 * 8, 1);
            mbar_wait(sb + BAR_KVE + 0 * 8, 0); mbar_wait(sb + BAR_KVE + 1 * 8, 0);
            wait_count(&g_boflag[r * 2 + half], e1 * 8);
            TRACE(13);
            fence_async();
#pragma unroll 1
            for (int kb = 0; kb < 7; kb++) {
                mbar_expect(sb + BAR_OBF + kb * 8, 8192);
                tma_load(sb + OFF_KV + kb * 8192, &maps.oLd, kb * 64, SEQ + r * 128 + half * 64, sb + BAR_OBF + kb * 8);
            }
        } else if (tid == 416) {
            mbar_wait(sb + BAR_B1D, 0);
            const uint32_t e1 = lds_u(sb + OFF_EPOCH);
            mbar_wait(sb + BAR_KVF + 3 * 8, 0);
            int st = 0; uint32_t epar = 1;
#pragma unroll 1
            for (int i = 0; i < 21; i++) {
                const int part = i / 7, kb = i - part * 7;
                const int wcol = (part == 2 ? 0 : (part + 1) * DM) + hp * 56;
                const uint32_t base = sb + OFF_A + st * A_STAGE, bar = sb + BAR_AF + st * 8;
                mbar_wait(sb + BAR_AE + st * 8, epar);
                mbar_expect(bar, A_STAGE);
                tma_load(base, &maps.xA, kb * 64, r * 128, bar);
                tma_load(base + 16384, &maps.wA, wcol, kb * 64, bar);
                if (++st == 3) { st = 0; epar ^= 1; }
            }
            wait_count(&g_aoflag[r], e1 * 8);
            fence_async();
#pragma unroll 1
            for (int kb = 0; kb < 7; kb++) {
                const uint32_t base = sb + OFF_A + st * A_STAGE, bar = sb + BAR_AF + st * 8;
                mbar_wait(sb + BAR_AE + st * 8, epar);
                mbar_expect(bar, A_STAGE);
                tma_load(base, &maps.oLd, kb * 64, r * 128 + half * 64, bar);
                tma_load(base + 8192, &maps.woA, cq * 112, kb * 64, bar);
                tma_load(base + 16384, &maps.woA, cq * 112 + 64, kb * 64, bar);
                if (++st == 3) { st = 0; epar ^= 1; }
            }
            mbar_wait(sb + BAR_ADONE, 0);
            mbar_expect(sb + BAR_WOB, 7 * 16384);
#pragma unroll 1
            for (int kb = 0; kb < 7; kb++) {
                tma_load(sb + OFF_A + kb * 16384, &maps.woB, cq * 112, kb * 64, sb + BAR_WOB);
                tma_load(sb + OFF_A + kb * 16384 + 8192, &maps.woB, cq * 112 + 64, kb * 64, sb + BAR_WOB);
            }
        }
    }
}

typedef CUresult (*EncodeFn)(CUtensorMap*, CUtensorMapDataType, cuuint32_t, void*, const cuuint64_t*, const cuuint64_t*,
                             const cuuint32_t*, const cuuint32_t*, CUtensorMapInterleave, CUtensorMapSwizzle,
                             CUtensorMapL2promotion, CUtensorMapFloatOOBfill);

void make_map(EncodeFn fn, CUtensorMap* m, const void* ptr, uint64_t cols, uint64_t rows, uint32_t box_cols, uint32_t box_rows, bool swz) {
    cuuint64_t dims[2] = {cols, rows};
    cuuint64_t strides[1] = {cols * 2};
    cuuint32_t box[2] = {box_cols, box_rows};
    cuuint32_t es[2] = {1, 1};
    fn(m, CU_TENSOR_MAP_DATA_TYPE_BFLOAT16, 2, const_cast<void*>(ptr), dims, strides, box, es, CU_TENSOR_MAP_INTERLEAVE_NONE,
       swz ? CU_TENSOR_MAP_SWIZZLE_128B : CU_TENSOR_MAP_SWIZZLE_NONE, CU_TENSOR_MAP_L2_PROMOTION_L2_128B, CU_TENSOR_MAP_FLOAT_OOB_FILL_NONE);
}

}

extern "C" void kernel_launch(void* const* d_in, const int* in_sizes, int n_in, void* d_out, int out_size) {
    (void)in_sizes; (void)n_in; (void)out_size;
    EncodeFn fn = nullptr;
    cudaDriverEntryPointQueryResult qr;
    cudaGetDriverEntryPoint("cuTensorMapEncodeTiled", reinterpret_cast<void**>(&fn), cudaEnableDefault, &qr);
    void* o_ptr = nullptr;
    cudaGetSymbolAddress(&o_ptr, g_o);
    Maps maps;
    make_map(fn, &maps.xA, d_in[0], DM, SEQ, 64, 128, true);
    make_map(fn, &maps.wA, d_in[1], 3 * DM, DM, 64, 64, true);
    make_map(fn, &maps.woA, d_in[2], DM, DM, 64, 64, true);
    make_map(fn, &maps.xB, d_in[3], DM, SEQ, 64, 128, true);
    make_map(fn, &maps.wB, d_in[4], 3 * DM, DM, 64, 64, true);
    make_map(fn, &maps.woB, d_in[5], DM, DM, 64, 64, true);
    make_map(fn, &maps.oLd, o_ptr, DM, 2 * SEQ, 64, 64, true);
    make_map(fn, &maps.oSt, o_ptr, DM, 2 * SEQ, 56, 64, false);
    make_map(fn, &maps.out, d_out, 2 * DM, SEQ, 112, 64, false);
    cudaFuncSetAttribute(fused_kernel, cudaFuncAttributeMaxDynamicSharedMemorySize, SMEM_BYTES);
    fused_kernel<<<NCTA, 512, SMEM_BYTES>>>(maps);
}
```

```cpp
#include <cuda.h>
#include <cuda_runtime.h>
#include <cuda_bf16.h>
#include <stdint.h>

namespace {

constexpr int SEQ = 2048, DM = 448;
constexpr int NCTA = 128;
#define NSPARE 0

constexpr uint32_t KV_SLOT   = 16384;
constexpr int      KV_SLOTS  = 6;
constexpr uint32_t OFF_KV    = 0;
constexpr uint32_t OFF_A     = 98304;
constexpr uint32_t OFF_B1    = 65536;
constexpr uint32_t B1_STAGE  = 40960;
constexpr uint32_t OFF_QST   = OFF_B1 + 2 * B1_STAGE;
constexpr uint32_t A_STAGE   = 24576;
constexpr uint32_t OFF_PQ    = OFF_A + 73728;
constexpr uint32_t OFF_PK    = OFF_A + 90112;
constexpr uint32_t OFF_AV    = OFF_A + 106496;
constexpr uint32_t OFF_KVB   = OFF_A + 122880;
constexpr uint32_t OFF_OB    = 2 * KV_SLOT;
constexpr uint32_t OFF_OUTB  = OFF_A + 114688;
constexpr uint32_t OFF_BAR   = 229376;
constexpr uint32_t BAR_B1F = OFF_BAR, BAR_B1E = OFF_BAR + 32, BAR_KVF = OFF_BAR + 64, BAR_KVE = OFF_BAR + 112,
                   BAR_AF = OFF_BAR + 160, BAR_AE = OFF_BAR + 184, BAR_OBF = OFF_BAR + 208, BAR_WOB = OFF_BAR + 264,
                   BAR_ADONE = OFF_BAR + 272, BAR_B1D = OFF_BAR + 280, BAR_NRM = OFF_BAR + 288, BAR_PUB = OFF_BAR + 296,
                   BAR_KNR = OFF_BAR + 304, BAR_QST = OFF_BAR + 312, BAR_OST = OFF_BAR + 320, BAR_GO = OFF_BAR + 328,
                   BAR_X1 = OFF_BAR + 336, BAR_Y2 = OFF_BAR + 344;
constexpr uint32_t OFF_EPOCH = OFF_BAR + 368;
constexpr uint32_t OFF_VBAD  = OFF_BAR + 372;
constexpr uint32_t OFF_LIMIT = OFF_BAR + 376;
constexpr uint32_t OFF_KN    = OFF_BAR + 384;
constexpr uint32_t OFF_QN    = OFF_BAR + 416;
constexpr uint32_t SMEM_BYTES = OFF_BAR + 1024;

constexpr float SAFE_BOUND_SQ = 40.f * 40.f * 0.9f;
constexpr float Q_SCALE = 0.18898223650461362f * 1.4426950408889634f;

__device__ uint4 g_kv[8 * 16 * 2 * (KV_SLOT / 16)];
__device__ __nv_bfloat16 g_o[2 * SEQ * DM];
__device__ float4 g_akv[8 * 16 * 4 * 128];
__device__ unsigned long long g_kvflag[8 * 32];
__device__ uint2 g_akv2[8 * 512];
__device__ unsigned int g_akvflag[8], g_akv2flag[8];
__device__ unsigned int g_aoflag[16];
__device__ unsigned int g_boflag[32 * 32];
__device__ unsigned long long g_done;
#define TRACE(i) do {} while (0)
#define GTRACE(i) do {} while (0)
#define ATRACE(i) do {} while (0)

#define OCNT 1
#define OSLEEP 0
#define ASTART 5
#define DESC_HI 0x40000040

%0, %1, %2, %3, %4, %5, %6, %7, %8, %9, %10, %11, %12, %13, %14, %15

__device__ __forceinline__ void wg_fence() { asm volatile("wgmma.fence.sync.aligned;" ::: "memory"); }
__device__ __forceinline__ void wg_commit() { asm volatile("wgmma.commit_group.sync.aligned;" ::: "memory"); }
template <int N> __device__ __forceinline__ void wg_wait() { asm volatile("wgmma.wait_group.sync.aligned %0;" ::"n"(N) : "memory"); }
template <int N> __device__ __forceinline__ void pin(float (&d)[N]) {
#pragma unroll
    for (int i = 0; i < N; i++) asm volatile("" : "+f"(d[i])::"memory");
}
template <int N> __device__ __forceinline__ void pin(uint32_t (&d)[N]) {
#pragma unroll
    for (int i = 0; i < N; i++) asm volatile("" : "+r"(d[i])::"memory");
}
__device__ __forceinline__ uint32_t dlo(uint32_t addr, uint32_t lbo = 0) { return ((addr >> 4) & 0x3FFF) | ((lbo >> 4) << 16); }
__device__ __forceinline__ float ex2(float x) { float y; asm("ex2.approx.ftz.f32 %0, %1;" : "=f"(y) : "f"(x)); return y; }
__device__ __forceinline__ float rcp(float x) { float y; asm("rcp.approx.ftz.f32 %0, %1;" : "=f"(y) : "f"(x)); return y; }
__device__ __forceinline__ uint32_t pack(float lo, float hi) { uint32_t r; asm("cvt.rn.bf16x2.f32 %0, %1, %2;" : "=r"(r) : "f"(hi), "f"(lo)); return r; }
__device__ __forceinline__ float bf_lo(uint32_t v) { return __uint_as_float(v << 16); }
__device__ __forceinline__ float bf_hi(uint32_t v) { return __uint_as_float(v & 0xFFFF0000u); }
__device__ __forceinline__ float rbf(float x) { return bf_hi(pack(0.f, x)); }

__device__ __forceinline__ void mbar_init(uint32_t bar, uint32_t cnt) { asm volatile("mbarrier.init.shared::cta.b64 [%0], %1;" ::"r"(bar), "r"(cnt)); }
__device__ __forceinline__ void mbar_expect(uint32_t bar, uint32_t bytes) { asm volatile("mbarrier.arrive.expect_tx.shared::cta.b64 _, [%0], %1;" ::"r"(bar), "r"(bytes) : "memory"); }
__device__ __forceinline__ void mbar_arrive(uint32_t bar) { asm volatile("mbarrier.arrive.shared::cta.b64 _, [%0];" ::"r"(bar) : "memory"); }
__device__ __forceinline__ void mbar_wait(uint32_t bar, uint32_t parity) {
    asm volatile(
        "{\n.reg .pred p;\n.reg .u32 c;\n"
        "mbarrier.try_wait.parity.shared::cta.b64 p, [%0], %1;\n@p bra W_DONE;\nmov.u32 c, 0;\n"
        "W_LOOP:\nmbarrier.try_wait.parity.shared::cta.b64 p, [%0], %1;\n@p bra W_DONE;\n"
        "add.u32 c, c, 1;\nsetp.lt.u32 p, c, 0x1000000;\n@p bra W_LOOP;\ntrap;\nW_DONE:\n}\n" ::"r"(bar), "r"(parity) : "memory");
}
#define BGWAIT 1
__device__ __forceinline__ void mbar_wait_bg(uint32_t bar, uint32_t parity) {
    asm volatile(
        "{\n.reg .pred p;\n.reg .u32 c;\nmov.u32 c, 0;\n"
        "W_LOOP:\nmbarrier.try_wait.parity.shared::cta.b64 p, [%0], %1, 20000;\n@p bra W_DONE;\n"
        "add.u32 c, c, 1;\nsetp.lt.u32 p, c, 0x100000;\n@p bra W_LOOP;\ntrap;\nW_DONE:\n}\n" ::"r"(bar), "r"(parity) : "memory");
}
__device__ __forceinline__ void warp_arrive(uint32_t bar) { if ((threadIdx.x & 31) == 0) mbar_arrive(bar); }
__device__ __forceinline__ void named_sync(int id) { asm volatile("bar.sync %0, 128;" ::"r"(id) : "memory"); }
__device__ __forceinline__ void fence_async() { asm volatile("fence.proxy.async.global;" ::: "memory"); }
__device__ __forceinline__ void fence_async_smem() { asm volatile("fence.proxy.async.shared::cta;" ::: "memory"); }

__device__ __forceinline__ void tma_load(uint32_t dst, const CUtensorMap* m, int c0, int c1, uint32_t bar) {
    asm volatile("cp.async.bulk.tensor.2d.shared::cluster.global.mbarrier::complete_tx::bytes [%0], [%1, {%3, %4}], [%2];"
                 ::"r"(dst), "l"(m), "r"(bar), "r"(c0), "r"(c1) : "memory");
}
__device__ __forceinline__ void tma_store(const CUtensorMap* m, int c0, int c1, uint32_t src) {
    asm volatile("cp.async.bulk.tensor.2d.global.shared::cta.bulk_group [%0, {%2, %3}], [%1];" ::"l"(m), "r"(src), "r"(c0), "r"(c1) : "memory");
}
__device__ __forceinline__ void bulk_load(uint32_t dst, const void* src, uint32_t bytes, uint32_t bar) {
    asm volatile("cp.async.bulk.shared::cluster.global.mbarrier::complete_tx::bytes [%0], [%1], %2, [%3];" ::"r"(dst), "l"(src), "r"(bytes), "r"(bar) : "memory");
}
__device__ __forceinline__ void bulk_store(void* dst, uint32_t src, uint32_t bytes) {
    asm volatile("cp.async.bulk.global.shared::cta.bulk_group [%0], [%1], %2;" ::"l"(dst), "r"(src), "r"(bytes) : "memory");
}
__device__ __forceinline__ void bulk_commit() { asm volatile("cp.async.bulk.commit_group;" ::: "memory"); }
__device__ __forceinline__ void bulk_wait_all() { asm volatile("cp.async.bulk.wait_group 0;" ::: "memory"); }
__device__ __forceinline__ void bulk_wait_read() { asm volatile("cp.async.bulk.wait_group.read 0;" ::: "memory"); }

__device__ __forceinline__ void red_release(unsigned int* p) { asm volatile("red.release.gpu.global.add.u32 [%0], 1;" ::"l"(p) : "memory"); }
__device__ __forceinline__ void red_after_bulk(unsigned int* p) { asm volatile("red.relaxed.gpu.global.add.u32 [%0], 1;" ::"l"(p) : "memory"); }
__device__ __forceinline__ void fence_acquire() { asm volatile("fence.acquire.gpu;" ::: "memory"); }
__device__ __forceinline__ void wait_count(const unsigned int* p, uint32_t target) {
    for (uint32_t n = 0;; n++) {
        uint32_t v;
        asm volatile("ld.relaxed.gpu.global.u32 %0, [%1];" : "=r"(v) : "l"(p) : "memory");
        if ((int32_t)(v - target) >= 0) break;
        if (n > (1u << 22)) __trap();
    }
    fence_acquire();
}
__device__ __forceinline__ void stsm4(uint32_t addr, uint32_t a, uint32_t b, uint32_t c, uint32_t d) {
    asm volatile("stmatrix.sync.aligned.m8n8.x4.shared.b16 [%0], {%1, %2, %3, %4};" ::"r"(addr), "r"(a), "r"(b), "r"(c), "r"(d) : "memory");
}
__device__ __forceinline__ void stsm2(uint32_t addr, uint32_t a, uint32_t b) {
    asm volatile("stmatrix.sync.aligned.m8n8.x2.shared.b16 [%0], {%1, %2};" ::"r"(addr), "r"(a), "r"(b) : "memory");
}
__device__ __forceinline__ void sts_u(uint32_t addr, uint32_t v) { asm volatile("st.shared.u32 [%0], %1;" ::"r"(addr), "r"(v) : "memory"); }
__device__ __forceinline__ uint32_t lds_u(uint32_t addr) { uint32_t v; asm volatile("ld.shared.u32 %0, [%1];" : "=r"(v) : "r"(addr) : "memory"); return v; }

__device__ __forceinline__ void store_tile16(uint32_t tile, int row0, const uint32_t (&v)[16]) {
    const int lane = threadIdx.x & 31;
    const int row = row0 + (lane & 7) + ((lane >> 3) & 1) * 8;
    const uint32_t base = tile + row * 128;
#pragma unroll
    for (int c = 0; c < 8; c += 2) stsm4(base + (((c + (lane >> 4)) ^ (lane & 7)) << 4), v[2 * c], v[2 * c + 1], v[2 * c + 2], v[2 * c + 3]);
}
__device__ __forceinline__ void spread_pair(const uint32_t (&p)[14], uint32_t (&v)[16], uint32_t pad_lo, uint32_t pad_hi) {
    const bool lo = (threadIdx.x & 2) == 0;
#pragma unroll
    for (int i = 0; i < 6; i++) { v[i] = p[i]; v[10 + i] = p[8 + i]; }
    v[6] = lo ? p[6] : pad_lo; v[7] = lo ? p[7] : pad_lo;
    v[8] = lo ? pad_hi : p[6]; v[9] = lo ? pad_hi : p[7];
}
__device__ __forceinline__ uint4 lds128(uint32_t addr) {
    uint4 v; asm volatile("ld.shared.v4.u32 {%0, %1, %2, %3}, [%4];" : "=r"(v.x), "=r"(v.y), "=r"(v.z), "=r"(v.w) : "r"(addr) : "memory"); return v;
}
__device__ __forceinline__ uint32_t bf2_sq(uint32_t x, uint32_t acc) { uint32_t y; asm("fma.rn.bf16x2 %0, %1, %1, %2;" : "=r"(y) : "r"(x), "r"(acc)); return y; }
__device__ __forceinline__ uint32_t bf2_absmax(uint32_t x, uint32_t acc) { uint32_t y; asm("max.NaN.xorsign.abs.bf16x2 %0, %1, %2;" : "=r"(y) : "r"(x), "r"(acc)); return y; }
__device__ __forceinline__ uint32_t bf2_add(uint32_t a, uint32_t b) { uint32_t y; asm("add.rn.bf16x2 %0, %1, %2;" : "=r"(y) : "r"(a), "r"(b)); return y; }
__device__ __forceinline__ void row_norms(const uint32_t (&ad)[8], uint32_t off, uint32_t& n0, uint32_t& n1) {
    uint4 x[8];
#pragma unroll
    for (int c = 0; c < 8; c++) x[c] = lds128(ad[c] + off);
    uint32_t s[8];
#pragma unroll
    for (int c = 0; c < 8; c++) s[c] = bf2_sq(x[c].w, bf2_sq(x[c].z, bf2_sq(x[c].y, bf2_sq(x[c].x, 0u))));
    const uint32_t a = bf2_add(bf2_add(s[0], s[1]), bf2_add(s[2], s[3])), b = bf2_add(bf2_add(s[4], s[5]), bf2_add(s[6], s[7]));
    n0 = __float_as_uint(bf_lo(a) + bf_hi(a));
    n1 = __float_as_uint(bf_lo(b) + bf_hi(b));
}

template <int N>
__device__ __forceinline__ void cta_norms(uint32_t table, float& n0, float& n1) {
    const uint32_t x = lds_u(table + (threadIdx.x & (2 * N - 1)) * 4);
    n0 = __uint_as_float(__reduce_max_sync(0xffffffffu, (threadIdx.x & 1) ? 0u : x));
    n1 = __uint_as_float(__reduce_max_sync(0xffffffffu, (threadIdx.x & 1) ? x : 0u));
}
__device__ __forceinline__ void lower_limit(uint32_t sb, uint32_t t) { asm volatile("red.shared.min.u32 [%0], %1;" ::"r"(sb + OFF_LIMIT), "r"(t) : "memory"); }

__device__ __forceinline__ void qk(float (&S)[32], const uint32_t (&Q)[8], uint32_t klo) {
    mma_rs_n64_k(S, Q[0], Q[1], Q[2], Q[3], klo, 0);
    mma_rs_n64_k(S, Q[4], Q[5], Q[6], Q[7], klo + 2, 1);
}
__device__ __forceinline__ void pv(float (&O)[16], const uint32_t (&P)[16], uint32_t vlo) {
#pragma unroll
    for (int s = 0; s < 4; s++) mma_rs_n32_n(O, P[4 * s], P[4 * s + 1], P[4 * s + 2], P[4 * s + 3], vlo + s * 128, 1);
}
template <bool SAFE>
__device__ __forceinline__ void softmax_tile(float (&S)[32], uint32_t (&P)[16], float (&O)[16], float (&m)[2]) {
    if (SAFE) {
#pragma unroll
        for (int j = 0; j < 16; j++) P[j] = pack(ex2(S[2 * j]), ex2(S[2 * j + 1]));
    } else {
        float m0 = m[0], m1 = m[1];
#pragma unroll
        for (int j = 0; j < 8; j++) { m0 = fmaxf(m0, fmaxf(S[4 * j], S[4 * j + 1])); m1 = fmaxf(m1, fmaxf(S[4 * j + 2], S[4 * j + 3])); }
        m0 = fmaxf(m0, __shfl_xor_sync(0xffffffffu, m0, 1)); m1 = fmaxf(m1, __shfl_xor_sync(0xffffffffu, m1, 1));
        m0 = fmaxf(m0, __shfl_xor_sync(0xffffffffu, m0, 2)); m1 = fmaxf(m1, __shfl_xor_sync(0xffffffffu, m1, 2));
        const float s0 = ex2(m[0] - m0), s1 = ex2(m[1] - m1);
        m[0] = m0; m[1] = m1;
#pragma unroll
        for (int j = 0; j < 4; j++) { O[4 * j] *= s0; O[4 * j + 1] *= s0; O[4 * j + 2] *= s1; O[4 * j + 3] *= s1; }
#pragma unroll
        for (int j = 0; j < 8; j++) {
            P[2 * j] = pack(ex2(S[4 * j] - m0), ex2(S[4 * j + 1] - m0));
            P[2 * j + 1] = pack(ex2(S[4 * j + 2] - m1), ex2(S[4 * j + 3] - m1));
        }
    }
}

struct Att {
    float S0[32], S1[32], O0[16], O1[16], m0[2], m1[2];
    uint32_t P0[16], P1[16], Q0[8], Q1[8];
    uint32_t sb, kb;
    bool lead;

    template <int SLOT, int MODE>
    __device__ __forceinline__ uint32_t step_safe(uint32_t npar) {
        constexpr int NS = (SLOT + 1) % KV_SLOTS, PS = (SLOT + KV_SLOTS - 1) % KV_SLOTS;
        const uint32_t kc = kb + SLOT * 1024, kn = kb + NS * 1024, vp = kb + PS * 1024 + 512;
        uint32_t limit;
        wg_fence(); qk(S1, Q1, kc + 4); wg_commit();
        wg_wait<1>(); pin(O0); pin(P0);
        pv(O1, P1, vp + 4); wg_commit();
        softmax_tile<true>(S0, P0, O0, m0);
        pin(P0);
        if (MODE != 2) {
            mbar_wait(sb + BAR_KVF + NS * 8, npar);
            if (MODE == 1) mbar_wait(sb + BAR_NRM, 0);
            limit = lds_u(sb + OFF_LIMIT);
            wg_wait<1>(); pin(S1);
            wg_fence(); qk(S0, Q0, kn); wg_commit();
            wg_wait<1>(); pin(O1); pin(P1);
            if (lead) mbar_arrive(sb + BAR_KVE + PS * 8);
            pv(O0, P0, kc + 512); wg_commit();
            softmax_tile<true>(S1, P1, O1, m1);
            pin(P1);
            if (SLOT == 1) { wg_wait<0>(); pin(O0); } else wg_wait<1>();
            pin(S0);
        } else {
            wg_wait<0>(); pin(S1); pin(O1); pin(P1);
            if (lead) mbar_arrive(sb + BAR_KVE + PS * 8);
            wg_fence(); pv(O0, P0, kc + 512); wg_commit();
            softmax_tile<true>(S1, P1, O1, m1);
            pin(P1);
            mbar_wait(sb + BAR_KVF + NS * 8, npar);
            limit = lds_u(sb + OFF_LIMIT);
            wg_fence(); qk(S0, Q0, kn); wg_commit();
            wg_wait<0>(); pin(S0); pin(O0);
        }
        return limit;
    }
    __device__ __forceinline__ void step_max(int slot, int nslot, int pslot, uint32_t npar, bool release) {
        const uint32_t kc = kb + slot * 1024, kn = kb + nslot * 1024, vp = kb + pslot * 1024 + 512;
        wg_fence(); pv(O1, P1, vp + 4); qk(S1, Q1, kc + 4); wg_commit();
        softmax_tile<false>(S0, P0, O0, m0);
        pin(P0); pin(O0);
        mbar_wait(sb + BAR_KVF + nslot * 8, npar);
        wg_wait<0>(); pin(S1); pin(O1);
        wg_fence(); pv(O0, P0, kc + 512); qk(S0, Q0, kn); wg_commit();
        if (lead && release) mbar_arrive(sb + BAR_KVE + pslot * 8);
        softmax_tile<false>(S1, P1, O1, m1);
        pin(P1); pin(O1);
        wg_wait<0>(); pin(S0); pin(O0);
    }
};

__device__ __forceinline__ uint32_t phi2(float a, float b) {
    uint32_t e = pack(ex2(a * 1.4426950408889634f), ex2(b * 1.4426950408889634f)), p;
    asm("min.NaN.bf16x2 %0, %0, %1;" : "+r"(e) : "r"(0x3F803F80u));
    asm("cvt.rn.relu.bf16x2.f32 %0, %1, %2;" : "=r"(p) : "f"(b), "f"(a));
    return bf2_add(bf2_add(p, e), 0x35863586u);
}

__device__ __forceinline__ void store_out(const float (&acc)[56], uint32_t stage, const CUtensorMap* map, int col, int row) {
    const int lane = threadIdx.x & 31, w = (threadIdx.x >> 5) & 3;
    const uint32_t base = stage + (w * 16 + (lane & 7) + ((lane >> 3) & 1) * 8) * 224 + (lane >> 4) * 16;
#pragma unroll
    for (int c = 0; c < 14; c += 2)
        stsm4(base + c * 16, pack(acc[4 * c], acc[4 * c + 1]), pack(acc[4 * c + 2], acc[4 * c + 3]),
              pack(acc[4 * c + 4], acc[4 * c + 5]), pack(acc[4 * c + 6], acc[4 * c + 7]));
    fence_async_smem();
    named_sync(3);
    if ((threadIdx.x & 127) == 0) { tma_store(map, col, row, stage); bulk_commit(); bulk_wait_read(); }
}
__device__ __forceinline__ void store_pair112(uint32_t stage, int row0, const uint32_t (&p)[14]) {
    const int lane = threadIdx.x & 31;
    const uint32_t base = stage + (row0 + (lane & 7) + ((lane >> 3) & 1) * 8) * 112;
    const uint32_t b4 = base + (lane >> 4) * 16;
    stsm4(b4, p[0], p[1], p[2], p[3]);
    stsm4(b4 + 32, p[4], p[5], p[6], p[7]);
    stsm4(b4 + 64, p[8], p[9], p[10], p[11]);
    stsm2(base + 96, p[12], p[13]);
}

struct Maps { CUtensorMap xA, wA, woA, xB, wB, woB, oLd, oSt, out; const uint8_t *pxA, *pwA, *pwoA, *pwoB; };

__global__ void __launch_bounds__(512, 1) fused_kernel(const __grid_constant__ Maps maps) {
    extern __shared__ __align__(1024) uint8_t smem_raw[];
    const uint32_t sb = (uint32_t)__cvta_generic_to_shared(smem_raw);
    const int tid = threadIdx.x;
    const int wg = __shfl_sync(0xffffffffu, tid >> 7, 0);
#define MAPR 2
    const int bid = blockIdx.x;
    const int r = bid >> 3, hp = bid & 7;
    const int half = hp >> 2, cq = hp & 3;

    const int wcol = hp * 56 - (hp & 1) * 8;
    const uint32_t wsh = hp & 1;
    auto b1_issue = [&](int kb) {
        const uint32_t st = sb + OFF_B1 + (kb & 3) * B1_STAGE, bar = sb + BAR_B1F + (kb & 3) * 8;
        mbar_expect(bar, B1_STAGE);
        tma_load(st, &maps.xB, kb * 64, r * 128, bar);
#pragma unroll
        for (int p = 0; p < 3; p++) tma_load(st + 16384 + p * 8192, &maps.wB, p * DM + wcol, kb * 64, bar);
    };

    if ((tid >> 5) == 12) {
        if (tid == 384) {
            TRACE(0); GTRACE(62);
            if (sb & 1023) __trap();
#pragma unroll
            for (int i = 0; i < 4; i++) mbar_init(sb + BAR_B1F + i * 8, 1);
#pragma unroll
            for (int i = 0; i < 3; i++) mbar_init(sb + BAR_B1E + i * 8, 8);
#pragma unroll
            for (int i = 0; i < KV_SLOTS; i++) { mbar_init(sb + BAR_KVF + i * 8, 1); mbar_init(sb + BAR_KVE + i * 8, 8); }
#pragma unroll
            for (int i = 0; i < 3; i++) { mbar_init(sb + BAR_AF + i * 8, 1); mbar_init(sb + BAR_AE + i * 8, 4); }
#pragma unroll
            for (int i = 0; i < 7; i++) mbar_init(sb + BAR_OBF + i * 8, 1);
            mbar_init(sb + BAR_WOB, 1); mbar_init(sb + BAR_ADONE, 1); mbar_init(sb + BAR_B1D, 8);
            mbar_init(sb + BAR_NRM, 4); mbar_init(sb + BAR_PUB, 1); mbar_init(sb + BAR_KNR, 4); mbar_init(sb + BAR_QST, 8); mbar_init(sb + BAR_OST, 2); mbar_init(sb + BAR_GO, 1);
            mbar_init(sb + BAR_X1, 1); mbar_init(sb + BAR_Y2, 1);
            sts_u(sb + OFF_VBAD, 0);
            asm volatile("st.shared.u32 [%0], 32;" ::"r"(sb + OFF_LIMIT) : "memory");
            asm volatile("fence.mbarrier_init.release.cluster;" ::: "memory");
            fence_async_smem();
            b1_issue(0);
        }
        __syncwarp();
        asm volatile("bar.arrive 0, 512;" ::: "memory");
    } else {
        asm volatile("bar.sync 0, 512;" ::: "memory");
    }

    if (wg < 2) {
        asm volatile("setmaxnreg.inc.sync.aligned.u32 176;");
        const int lane = tid & 31, w = (tid >> 5) & 3;
        Att a;
        a.sb = sb; a.kb = dlo(sb + OFF_KV); a.lead = lane == 0;
        {
            float acc[92];
#pragma unroll 1
            for (int kb = 0; kb < 7; kb++) {
                const uint32_t st = sb + OFF_B1 + (kb & 3) * B1_STAGE;
                mbar_wait(sb + BAR_B1F + (kb & 3) * 8, kb >> 2);
                const uint32_t da = dlo(st + wg * 8192), db = dlo(st + 16384, 8192) + wsh;
                wg_fence();
#pragma unroll
                for (int ks = 0; ks < 4; ks++) mma_ss_n184_kn(acc, da + ks * 2, db + ks * 128, (kb | ks) != 0);
                wg_commit();
                if (kb > 0) { wg_wait<1>(); if (kb < 4) warp_arrive(sb + BAR_B1E + (kb - 1) * 8); }
            }
#pragma unroll
            for (int i = 0; i < 16; i++) { a.O0[i] = 0.f; a.O1[i] = 0.f; a.P1[i] = 0u; }
            wg_wait<0>(); pin(acc);
            pin(a.O0); pin(a.O1); pin(a.P1);
            warp_arrive(sb + BAR_B1D);
            if (tid == 0) TRACE(2);
            uint32_t p[14], v[16];
#pragma unroll
            for (int i = 0; i < 14; i++) p[i] = pack(acc[32 + 2 * i], acc[33 + 2 * i]);
            spread_pair(p, v, 0u, 0u);
            store_tile16(sb + OFF_KV + wg * KV_SLOT, w * 16, v);
#pragma unroll
            for (int i = 0; i < 14; i++) p[i] = pack(acc[64 + 2 * i], acc[65 + 2 * i]);
            spread_pair(p, v, (lane & 3) == 2 ? 0x3F80u : 0u, (lane & 3) == 0 ? 0x3F80u : 0u);
            store_tile16(sb + OFF_KV + wg * KV_SLOT + 8192, w * 16, v);
            {
                uint32_t m[7];
#pragma unroll
                for (int i = 0; i < 7; i++) m[i] = bf2_absmax(p[2 * i], p[2 * i + 1]);
                const uint32_t vm = bf2_absmax(bf2_absmax(bf2_absmax(m[0], m[1]), bf2_absmax(m[2], m[3])), bf2_absmax(bf2_absmax(m[4], m[5]), m[6]));
                if ((vm & 0x7FFFu) > 0x5D00u || (vm & 0x7FFF0000u) > 0x5D000000u) sts_u(sb + OFF_VBAD, 1);
            }
            fence_async_smem();
            named_sync(1 + wg);
            if ((tid & 127) == 0) mbar_arrive(sb + BAR_KVF + wg * 8);
            if (tid == 0) TRACE(39);
#pragma unroll
            for (int i = 0; i < 14; i++) p[i] = pack(acc[2 * i] * Q_SCALE, acc[2 * i + 1] * Q_SCALE);
            spread_pair(p, v, 0u, 0u);
#pragma unroll
            for (int i = 0; i < 8; i++) { a.Q0[i] = v[i]; a.Q1[i] = v[8 + i]; }
            pin(a.Q0); pin(a.Q1);
            mbar_wait(sb + BAR_KVF, 0);
            if (tid == 0) TRACE(3);
            wg_fence(); qk(a.S0, a.Q0, a.kb); wg_commit();
            store_tile16(sb + OFF_QST + wg * 8192, w * 16, v);
            __syncwarp();
            if (lane == 0) mbar_arrive(sb + BAR_QST);
        }
        wg_wait<0>(); pin(a.S0);
        uint32_t t = 0;
        if (tid == 0) TRACE(32);
#define STEP_TRACE
#define SAFE_STEP(S, M, P) { const uint32_t lim = a.step_safe<S, M>(P); STEP_TRACE; if (++t >= lim) { wg_wait<0>(); pin(a.O0); break; } }
        do {
            SAFE_STEP(0, 1, 0)
            SAFE_STEP(1, 2, 0)
            uint32_t par = 0;
#pragma unroll 1
            for (;;) {
                SAFE_STEP(2, 0, par) SAFE_STEP(3, 0, par) SAFE_STEP(4, 0, par)
                par ^= 1;
                SAFE_STEP(5, 0, par) SAFE_STEP(0, 0, par) SAFE_STEP(1, 0, par)
            }
        } while (0);
        if (t < 32) {
            float m_init = 0.f;
            const bool redo = lds_u(sb + OFF_LIMIT) == 0;
            if (redo) {
                m_init = __int_as_float(0xff800000);
                t = 0;
#pragma unroll
                for (int i = 0; i < 16; i++) { a.O0[i] = 0.f; a.O1[i] = 0.f; a.P1[i] = 0u; }
                pin(a.O0); pin(a.O1); pin(a.P1);
                wg_fence(); qk(a.S0, a.Q0, a.kb); wg_commit(); wg_wait<0>(); pin(a.S0);
            }
            a.m0[0] = a.m0[1] = a.m1[0] = a.m1[1] = m_init;
#pragma unroll 1
            for (; t < 32; t++) a.step_max(t % 6, (t + 1) % 6, (t + 5) % 6, ((t + 1) / 6) & 1, t > 0);
        }
        wg_fence(); pv(a.O1, a.P1, a.kb + 1 * 1024 + 512 + 4); wg_commit(); wg_wait<0>(); pin(a.O1);
        warp_arrive(sb + BAR_KVE + 1 * 8);
        if (tid == 0) TRACE(8);
        if (tid == 128) TRACE(34);
        {
            const int q0 = lane & ~3;
            const float i00 = rcp(__shfl_sync(0xffffffffu, a.O0[12], q0 | 2)), i01 = rcp(__shfl_sync(0xffffffffu, a.O0[14], q0 | 2));
            const float i10 = rcp(__shfl_sync(0xffffffffu, a.O1[0], q0)), i11 = rcp(__shfl_sync(0xffffffffu, a.O1[2], q0));
            uint32_t p[14];
#pragma unroll
            for (int j = 0; j < 3; j++) {
                p[2 * j] = pack(a.O0[4 * j] * i00, a.O0[4 * j + 1] * i00);
                p[2 * j + 1] = pack(a.O0[4 * j + 2] * i01, a.O0[4 * j + 3] * i01);
                p[8 + 2 * j] = pack(a.O1[4 * j + 4] * i10, a.O1[4 * j + 5] * i10);
                p[9 + 2 * j] = pack(a.O1[4 * j + 6] * i11, a.O1[4 * j + 7] * i11);
            }
            const bool lo = (lane & 2) == 0;
            p[6] = lo ? pack(a.O0[12] * i00, a.O0[13] * i00) : pack(a.O1[0] * i10, a.O1[1] * i10);
            p[7] = lo ? pack(a.O0[14] * i01, a.O0[15] * i01) : pack(a.O1[2] * i11, a.O1[3] * i11);
            const uint32_t stage = sb + OFF_OUTB + wg * 7168;
            mbar_wait(sb + BAR_ADONE, 0);
            store_pair112(stage, w * 16, p);
            fence_async_smem();
            named_sync(1 + wg);
            if ((tid & 127) == 0) {
                if (tid == 0) TRACE(33); else TRACE(35);
                tma_store(&maps.oSt, hp * 56, SEQ + r * 128 + wg * 64, stage);
                bulk_commit(); bulk_wait_all();
                red_after_bulk(&g_boflag[(r * 2 + wg) * 32]);
                mbar_arrive(sb + BAR_OST);
                if (tid == 0) TRACE(9); else TRACE(36);
            }
        }
    } else if (wg == 2) {
        asm volatile("setmaxnreg.dec.sync.aligned.u32 120;");
        const int lane = tid & 31, w = (tid >> 5) & 3, t128 = tid & 127;
        {
            uint32_t ad[8];
#pragma unroll
            for (int c = 0; c < 8; c++) ad[c] = sb + (t128 & 63) * 128 + ((c ^ (t128 & 7)) << 4);
            const uint32_t koff = OFF_KV + (t128 >> 6) * KV_SLOT, qoff = OFF_QST + (t128 >> 6) * 8192;
            pin(ad);
            uint32_t n0, n1;
            mbar_wait(sb + BAR_KVF + (t128 >> 6) * 8, 0);
            row_norms(ad, koff, n0, n1);
            if (lds_u(sb + OFF_VBAD) != 0) n0 = n1 = 0x7f800000u;
            n0 = __reduce_max_sync(0xffffffffu, n0); n1 = __reduce_max_sync(0xffffffffu, n1);
            if (lane == 0) { sts_u(sb + OFF_KN + w * 8, n0); sts_u(sb + OFF_KN + w * 8 + 4, n1); mbar_arrive(sb + BAR_KNR); }
            if (t128 == 0) TRACE(43);
            mbar_wait(sb + BAR_QST, 0);
            row_norms(ad, qoff, n0, n1);
            n0 = __reduce_max_sync(0xffffffffu, n0); n1 = __reduce_max_sync(0xffffffffu, n1);
            mbar_wait(sb + BAR_KNR, 0);
            float k0, k1;
            cta_norms<4>(sb + OFF_KN, k0, k1);
            if (lane == 0) {
                sts_u(sb + OFF_QN + w * 8, n0); sts_u(sb + OFF_QN + w * 8 + 4, n1);
                if (!(__uint_as_float(n0) * k0 <= SAFE_BOUND_SQ && __uint_as_float(n1) * k1 <= SAFE_BOUND_SQ)) lower_limit(sb, 0);
                mbar_arrive(sb + BAR_NRM);
            }
            if (t128 == 0) TRACE(37);
        }
        int st = 0; uint32_t par = 0;
#pragma unroll 1
        for (int part = 0; part < 3; part++) {
            float acc0[28], acc1[28];
#pragma unroll 1
            for (int kb = 0; kb < 7; kb++) {
                const uint32_t base = sb + OFF_A + st * A_STAGE;
                mbar_wait_bg(sb + BAR_AF + st * 8, par);
                if (t128 == 32) ATRACE(part * 7 + kb);
                const uint32_t da = dlo(base), db = dlo(base + 16384) + wsh;
                wg_fence();
#pragma unroll
                for (int ks = 0; ks < 4; ks++) {
                    mma_ss_n56_kn(acc0, da + ks * 2, db + ks * 128, (kb | ks) != 0);
                    mma_ss_n56_kn(acc1, da + 512 + ks * 2, db + ks * 128, (kb | ks) != 0);
                }
                wg_commit(); wg_wait<0>();
                warp_arrive(sb + BAR_AE + st * 8);
                if (t128 == 32) ATRACE(32 + part * 7 + kb);
                if (++st == 3) { st = 0; par ^= 1; }
            }
            pin(acc0); pin(acc1);
            const bool is_v = (part == 1);
            if (t128 == 0 && part == 2) TRACE(44);
            const uint32_t tile = sb + (part == 0 ? OFF_PK : is_v ? OFF_AV : OFF_PQ);
            const uint32_t pad_lo = (is_v && (lane & 3) == 2) ? 0x3F80u : 0u, pad_hi = (is_v && (lane & 3) == 0) ? 0x3F80u : 0u;
            uint32_t p[14], v[16];
#pragma unroll
            for (int i = 0; i < 14; i++) p[i] = is_v ? pack(acc0[2 * i], acc0[2 * i + 1]) : phi2(acc0[2 * i], acc0[2 * i + 1]);
            spread_pair(p, v, pad_lo, pad_hi);
            store_tile16(tile, w * 16, v);
#pragma unroll
            for (int i = 0; i < 14; i++) p[i] = is_v ? pack(acc1[2 * i], acc1[2 * i + 1]) : phi2(acc1[2 * i], acc1[2 * i + 1]);
            spread_pair(p, v, pad_lo, pad_hi);
            store_tile16(tile, 64 + w * 16, v);
            if (is_v) {
                fence_async_smem();
                named_sync(3);
                float d[32];
                const uint32_t da = dlo(sb + OFF_PK), db = dlo(sb + OFF_AV);
                wg_fence();
#pragma unroll
                for (int ks = 0; ks < 8; ks++) mma_ss_n64_mn(d, da + ks * 128, db + ks * 128, ks != 0);
                wg_commit(); wg_wait<0>(); pin(d);
#pragma unroll
                for (int i = 0; i < 4; i++)
                    asm volatile("st.shared.v4.f32 [%0], {%1, %2, %3, %4};" ::"r"(sb + OFF_KVB + i * 2048 + t128 * 16),
                                 "f"(w < 2 ? d[4 * i] : d[16 + 4 * i]), "f"(w < 2 ? d[4 * i + 1] : d[17 + 4 * i]),
                                 "f"(w < 2 ? d[4 * i + 2] : d[18 + 4 * i]), "f"(w < 2 ? d[4 * i + 3] : d[19 + 4 * i]) : "memory");
                fence_async_smem();
                named_sync(3);
                if (t128 == 0) { mbar_arrive(sb + BAR_X1); TRACE(16); }
            }
        }
        if (t128 == 0) TRACE(17);
        mbar_wait_bg(sb + BAR_Y2, 0);
        {
            uint32_t v[16];
#pragma unroll
            for (int i = 0; i < 4; i++) {
                uint2 x;
                asm volatile("ld.shared.v2.u32 {%0, %1}, [%2];" : "=r"(x.x), "=r"(x.y) : "r"(sb + OFF_AV + i * 1024 + t128 * 8) : "memory");
                v[2 * i] = w < 2 ? x.x : 0u; v[2 * i + 1] = w < 2 ? x.y : 0u;
                v[8 + 2 * i] = w < 2 ? 0u : x.x; v[9 + 2 * i] = w < 2 ? 0u : x.y;
            }
            store_tile16(sb + OFF_KVB, w * 16, v);
        }
        fence_async_smem();
        named_sync(3);
        {
            float n0[32], n1[32];
            const uint32_t da = dlo(sb + OFF_PQ), db = dlo(sb + OFF_KVB);
            wg_fence();
#pragma unroll
            for (int ks = 0; ks < 4; ks++) {
                mma_ss_n64_kn(n0, da + ks * 2, db + ks * 128, ks != 0);
                mma_ss_n64_kn(n1, da + 512 + ks * 2, db + ks * 128, ks != 0);
            }
            wg_commit(); wg_wait<0>(); pin(n0); pin(n1);
            const int q0 = lane & ~3;
            const bool lo = (lane & 2) == 0;
            auto finish = [&](const float (&n)[32], int row0) {
                const float i00 = rcp(rbf(rbf(__shfl_sync(0xffffffffu, n[12], q0 | 2)) + 1e-6f));
                const float i01 = rcp(rbf(rbf(__shfl_sync(0xffffffffu, n[14], q0 | 2)) + 1e-6f));
                const float i10 = rcp(rbf(rbf(__shfl_sync(0xffffffffu, n[16], q0)) + 1e-6f));
                const float i11 = rcp(rbf(rbf(__shfl_sync(0xffffffffu, n[18], q0)) + 1e-6f));
                auto sc = [](float a, float b, float inv) { return pack(a * inv, b * inv); };
                uint32_t p[14];
#pragma unroll
                for (int j = 0; j < 3; j++) {
                    p[2 * j] = sc(n[4 * j], n[4 * j + 1], i00);
                    p[2 * j + 1] = sc(n[4 * j + 2], n[4 * j + 3], i01);
                    p[8 + 2 * j] = sc(n[20 + 4 * j], n[21 + 4 * j], i10);
                    p[9 + 2 * j] = sc(n[22 + 4 * j], n[23 + 4 * j], i11);
                }
                p[6] = sc(lo ? n[12] : n[16], lo ? n[13] : n[17], lo ? i00 : i10);
                p[7] = sc(lo ? n[14] : n[18], lo ? n[15] : n[19], lo ? i01 : i11);
                store_pair112(sb + OFF_PK, row0, p);
            };
            finish(n0, w * 16);
            finish(n1, 64 + w * 16);
            fence_async_smem();
            named_sync(3);
            if (t128 == 0) {
                tma_store(&maps.oSt, hp * 56, r * 128, sb + OFF_PK);
                tma_store(&maps.oSt, hp * 56, r * 128 + 64, sb + OFF_PK + 64 * 112);
                bulk_commit(); bulk_wait_all();
                red_after_bulk(&g_aoflag[r]);
                TRACE(18);
            }
        }
        {
            float acc[56];
#pragma unroll 1
            for (int kb = 0; kb < 7; kb++) {
                const uint32_t base = sb + OFF_A + st * A_STAGE;
                mbar_wait_bg(sb + BAR_AF + st * 8, par);
                const uint32_t da = dlo(base), db = dlo(base + 8192, 8192);
                wg_fence();
#pragma unroll
                for (int ks = 0; ks < 4; ks++) mma_ss_n112_kn(acc, da + ks * 2, db + ks * 128, (kb | ks) != 0);
                wg_commit(); wg_wait<0>();
                if (++st == 3) { st = 0; par ^= 1; }
                if (kb < 4) warp_arrive(sb + BAR_AE + (st == 0 ? 2 : st - 1) * 8);
            }
            pin(acc);
            store_out(acc, sb + OFF_AV, &maps.out, cq * 112, r * 128 + half * 64);
            if (t128 == 0) { mbar_arrive(sb + BAR_ADONE); TRACE(19); }
        }
        {
            float acc[56];
            mbar_wait_bg(sb + BAR_WOB, 0);
#pragma unroll 1
            for (int kb = 0; kb < 7; kb++) {
                mbar_wait(sb + BAR_OBF + kb * 8, 0);
                if (t128 == 0 && kb == 0) TRACE(20);
                const uint32_t da = dlo(sb + OFF_OB + kb * 8192), db = dlo(sb + OFF_A + kb * 16384, 8192);
                wg_fence();
#pragma unroll
                for (int ks = 0; ks < 4; ks++) mma_ss_n112_kn(acc, da + ks * 2, db + ks * 128, (kb | ks) != 0);
                wg_commit();
            }
            wg_wait<0>(); pin(acc);
            if (t128 == 0) TRACE(21);
            mbar_wait(sb + BAR_OST, 0);
            store_out(acc, sb + OFF_OUTB, &maps.out, DM + cq * 112, r * 128 + half * 64);
            if (t128 == 0) { atomicAdd(&g_done, 1ull); TRACE(22); GTRACE(63); }
        }
    } else {
        asm volatile("setmaxnreg.dec.sync.aligned.u32 40;");
        if ((tid >> 5) == 12) {
            const int lane = tid & 31;
            const uint8_t* kvg = reinterpret_cast<const uint8_t*>(g_kv) + (size_t)hp * 32 * KV_SLOT;
            unsigned long long* flags = g_kvflag + hp * 32;
            if (lane == 0) {
                unsigned long long done0;
                asm volatile("ld.relaxed.gpu.global.u64 %0, [%1];" : "=l"(done0) : "l"(&g_done) : "memory");
#pragma unroll 1
                for (int kb = 1; kb < 4; kb++) b1_issue(kb);
                TRACE(1);
                const uint32_t e1 = (uint32_t)(done0 / NCTA) + 1;
                asm volatile("st.shared.u32 [%0], %1;" ::"r"(sb + OFF_EPOCH), "r"(e1) : "memory");
#pragma unroll 1
                for (int kb = 4; kb < 7; kb++) {
                    mbar_wait_bg(sb + BAR_B1E + (kb & 3) * 8, 0);
                    b1_issue(kb);
                }
                mbar_wait(sb + BAR_KVF, 0);
                bulk_store(const_cast<uint8_t*>(kvg) + (size_t)r * KV_SLOT, sb + OFF_KV, KV_SLOT);
                bulk_commit();
                mbar_wait(sb + BAR_KNR, 0);
                uint32_t k0 = 0, k1 = 0;
#pragma unroll
                for (int i = 0; i < 4; i++) { k0 = max(k0, lds_u(sb + OFF_KN + i * 8)); k1 = max(k1, lds_u(sb + OFF_KN + i * 8 + 4)); }
                const uint32_t nb = (min(k0 + 0xFFFFu, 0x7FFFFFFFu) >> 16) | (min(k1 + 0xFFFFu, 0x7FFFFFFFu) & 0xFFFF0000u);
                const unsigned long long val = ((unsigned long long)e1 << 32) | nb;
                bulk_wait_all();
                asm volatile("st.relaxed.gpu.global.u64 [%0], %1;" ::"l"(flags + r), "l"(val) : "memory");
                TRACE(14);
                mbar_wait_bg(sb + BAR_GO, 0);
                bulk_store(const_cast<uint8_t*>(kvg) + (size_t)(16 + r) * KV_SLOT, sb + OFF_KV + KV_SLOT, KV_SLOT);
                bulk_commit();
                bulk_wait_all();
                asm volatile("st.relaxed.gpu.global.u64 [%0], %1;" ::"l"(flags + 16 + r), "l"(val) : "memory");
                mbar_arrive(sb + BAR_PUB);
                TRACE(10);
            }
        } else if ((tid >> 5) == 14) {
            const int lane = tid & 31;
            const uint8_t* kvg = reinterpret_cast<const uint8_t*>(g_kv) + (size_t)hp * 32 * KV_SLOT;
            const unsigned long long* flags = g_kvflag + hp * 32;
            mbar_wait_bg(sb + BAR_B1F + 0 * 8, 0);
            mbar_wait_bg(sb + BAR_B1F + 0 * 8, 1);
            const uint32_t e1 = lds_u(sb + OFF_EPOCH);
            uint32_t todo = ~((1u << r) | (1u << (16 + r))), ready = 0, nb = 0;
            auto ld_flag = [&]() {
                unsigned long long v;
                asm volatile("ld.relaxed.gpu.global.u64 %0, [%1];" : "=l"(v) : "l"(flags + lane) : "memory");
                return v;
            };
            auto seen = [&](unsigned long long v) {
                nb = (uint32_t)v;
                ready = __ballot_sync(0xffffffffu, (uint32_t)(v >> 32) == e1);
                return (ready & todo) != 0;
            };
            auto poll_some = [&]() {
                for (uint32_t n = 0; !seen(ld_flag()); n++) if (n > (1u << 22)) __trap();
                fence_acquire();
                fence_async();
            };
            auto load_tile = [&](int slot, int tile) {
                asm volatile("mbarrier.expect_tx.relaxed.cta.shared::cta.b64 [%0], %1;" ::"r"(sb + BAR_KVF + slot * 8), "r"(KV_SLOT) : "memory");
                bulk_load(sb + OFF_KV + slot * KV_SLOT, kvg + (size_t)tile * KV_SLOT, KV_SLOT, sb + BAR_KVF + slot * 8);
            };
            uint32_t mine = 0;
            int t = 2, armed = 2;
            bool have_q = false;
            float q0 = 0.f, q1 = 0.f;
            auto arm = [&]() {
                if (lane >= armed && lane < t) {
                    if (!(q0 * bf_lo(mine) <= SAFE_BOUND_SQ && q1 * bf_hi(mine) <= SAFE_BOUND_SQ)) lower_limit(sb, lane);
                    mbar_arrive(sb + BAR_KVF + lane * 8);
                }
                armed = t;
            };
#pragma unroll 1
            for (uint32_t it = 0; t < KV_SLOTS; it++) {
                if (seen(ld_flag())) {
                    fence_acquire();
                    fence_async();
                    if (t == 2) { if (lane == 0) TRACE(42); mbar_wait(sb + BAR_B1D, 0); }
                    const uint32_t avail = ready & todo;
                    const int n = min(__popc(avail), KV_SLOTS - t);
                    const bool take = lane >= t && lane < t + n;
                    const int pick = take ? __fns(avail, 0, lane - t + 1) : 0;
                    const uint32_t tn = __shfl_sync(0xffffffffu, nb, pick);
                    if (take) { mine = tn; load_tile(lane, pick); }
                    todo &= ~__reduce_or_sync(0xffffffffu, take ? 1u << pick : 0u);
                    t += n;
                }
                if (armed < t && t < KV_SLOTS) {
                    if (!have_q) {
                        uint32_t ok;
                        asm volatile("{\n.reg .pred p;\nmbarrier.test_wait.parity.shared::cta.b64 p, [%1], 0;\nselp.u32 %0, 1, 0, p;\n}\n" : "=r"(ok) : "r"(sb + BAR_NRM) : "memory");
                        if (__all_sync(0xffffffffu, ok)) { have_q = true; cta_norms<4>(sb + OFF_QN, q0, q1); }
                    }
                    if (have_q) arm();
                }
                __syncwarp();
                if (it > (1u << 22)) __trap();
            }
            if (lane == 0) mbar_arrive(sb + BAR_GO);
            if (!have_q) { mbar_wait(sb + BAR_NRM, 0); cta_norms<4>(sb + OFF_QN, q0, q1); }
            arm();
            __syncwarp();
            if (lane == 0) TRACE(49);
            if ((ready & todo) != todo) {
                seen(ld_flag());
                fence_acquire();
                fence_async();
            }
            if (lane == 0) mbar_wait_bg(sb + BAR_PUB, 0);
            int slot = 0; uint32_t epar = 0;
#pragma unroll 1
            for (; t < 32; t++) {
                if ((ready & todo) == 0) poll_some();
                const int tile = __ffs(ready & todo) - 1;
                todo &= ~(1u << tile);
                const uint32_t tn = __shfl_sync(0xffffffffu, nb, tile);
                if (lane == 0) {
                    mbar_wait_bg(sb + BAR_KVE + slot * 8, slot == KV_SLOTS - 1 ? epar ^ 1 : epar);
                    load_tile(slot, tile);
                    if (!(q0 * bf_lo(tn) <= SAFE_BOUND_SQ && q1 * bf_hi(tn) <= SAFE_BOUND_SQ)) lower_limit(sb, t);
                    mbar_arrive(sb + BAR_KVF + slot * 8);
                    if (t < 9) TRACE(44 + t);
                }
                __syncwarp();
                if (++slot == KV_SLOTS) { slot = 0; epar ^= 1; }
            }
            if (lane == 0) {
                mbar_wait_bg(sb + BAR_KVE + 2 * 8, 0);
                mbar_arrive(sb + BAR_KVF + 2 * 8);
            }
            const unsigned int* oflags = g_boflag + (r * 2 + half) * 32 + (OCNT ? 0 : (lane & 7));
            const int ocol = lane * 64, orow = SEQ + r * 128 + half * 64;
            if (lane < 7) mbar_expect(sb + BAR_OBF + lane * 8, 8192);
            mbar_wait_bg(sb + BAR_KVE + 3 * 8, 0); mbar_wait_bg(sb + BAR_KVE + 4 * 8, 0); mbar_wait_bg(sb + BAR_KVE + 5 * 8, 1);
            {
                auto ld = [&]() { uint32_t v; asm volatile("ld.relaxed.gpu.global.u32 %0, [%1];" : "=r"(v) : "l"(oflags) : "memory"); return v; };
                for (uint32_t n = 0; !__all_sync(0xffffffffu, OCNT ? (int32_t)(ld() - e1 * 8) >= 0 : ld() == e1); n++) {
                    if (OSLEEP) __nanosleep(OSLEEP);
                    if (n > (1u << 22)) __trap();
                }
            }
            if (lane == 0) TRACE(13);
            fence_acquire();
            fence_async();
            if (lane < 7) tma_load(sb + OFF_OB + lane * 8192, &maps.oLd, ocol, orow, sb + BAR_OBF + lane * 8);
            if (lane == 0) TRACE(46);
        } else if ((tid >> 5) == 15) {
            const int lane = tid & 31;
            mbar_wait_bg(sb + BAR_X1, 0);
            const uint32_t e1 = lds_u(sb + OFF_EPOCH);
            if (lane == 0) {
                bulk_store(g_akv + (hp * 16 + r) * 512, sb + OFF_KVB, 8192);
                bulk_commit(); bulk_wait_all();
                red_after_bulk(&g_akvflag[hp]);
                wait_count(&g_akvflag[hp], e1 * 16);
            }
            __syncwarp();
            const float4* src = g_akv + hp * 16 * 512 + r * 32 + lane;
            float4 y = make_float4(0.f, 0.f, 0.f, 0.f);
#pragma unroll 1
            for (int i = 0; i < 4; i++, src += 2048) {
                const float4 x0 = __ldcg(src), x1 = __ldcg(src + 512), x2 = __ldcg(src + 1024), x3 = __ldcg(src + 1536);
                y.x += (x0.x + x1.x) + (x2.x + x3.x); y.y += (x0.y + x1.y) + (x2.y + x3.y);
                y.z += (x0.z + x1.z) + (x2.z + x3.z); y.w += (x0.w + x1.w) + (x2.w + x3.w);
            }
            g_akv2[hp * 512 + r * 32 + lane] = make_uint2(pack(y.x, y.y), pack(y.z, y.w));
            __syncwarp();
            if (lane == 0) {
                red_release(&g_akv2flag[hp]);
                wait_count(&g_akv2flag[hp], e1 * 16);
                fence_async();
                mbar_expect(sb + BAR_Y2, 4096);
                bulk_load(sb + OFF_AV, g_akv2 + hp * 512, 4096, sb + BAR_Y2);
                TRACE(45);
            }
        } else if (tid == 416) {
            mbar_wait_bg(sb + BAR_B1D, 0);
            const uint32_t e1 = lds_u(sb + OFF_EPOCH);
            mbar_wait_bg(sb + BAR_NRM, 0);
            mbar_wait_bg(sb + BAR_KVF + ASTART * 8, 0);
            int st = 0; uint32_t epar = 1;
#pragma unroll 1
            for (int i = 0; i < 21; i++) {
                const int part = i / 7, kb = i - part * 7;
                const int col = (part == 2 ? 0 : (part + 1) * DM) + wcol;
                const uint32_t base = sb + OFF_A + st * A_STAGE, bar = sb + BAR_AF + st * 8;
                mbar_wait_bg(sb + BAR_AE + st * 8, epar);
                mbar_expect(bar, A_STAGE);
                tma_load(base, &maps.xA, kb * 64, r * 128, bar);
                tma_load(base + 16384, &maps.wA, col, kb * 64, bar);
                ATRACE(64 + i);
                if (++st == 3) { st = 0; epar ^= 1; }
            }
            wait_count(&g_aoflag[r], e1 * 8);
            fence_async();
#pragma unroll 1
            for (int kb = 0; kb < 7; kb++) {
                const uint32_t base = sb + OFF_A + st * A_STAGE, bar = sb + BAR_AF + st * 8;
                mbar_wait_bg(sb + BAR_AE + st * 8, epar);
                mbar_expect(bar, A_STAGE);
                tma_load(base, &maps.oLd, kb * 64, r * 128 + half * 64, bar);
                tma_load(base + 8192, &maps.woA, cq * 112, kb * 64, bar);
                tma_load(base + 16384, &maps.woA, cq * 112 + 64, kb * 64, bar);
                if (++st == 3) { st = 0; epar ^= 1; }
            }
            mbar_wait_bg(sb + BAR_ADONE, 0);
            mbar_expect(sb + BAR_WOB, 7 * 16384);
#pragma unroll 1
            for (int kb = 0; kb < 7; kb++) {
                tma_load(sb + OFF_A + kb * 16384, &maps.woB, cq * 112, kb * 64, sb + BAR_WOB);
                tma_load(sb + OFF_A + kb * 16384 + 8192, &maps.woB, cq * 112 + 64, kb * 64, sb + BAR_WOB);
            }
        }
    }
}

typedef CUresult (*EncodeFn)(CUtensorMap*, CUtensorMapDataType, cuuint32_t, void*, const cuuint64_t*, const cuuint64_t*,
                             const cuuint32_t*, const cuuint32_t*, CUtensorMapInterleave, CUtensorMapSwizzle,
                             CUtensorMapL2promotion, CUtensorMapFloatOOBfill);

void make_map(EncodeFn fn, CUtensorMap* m, const void* ptr, uint64_t cols, uint64_t rows, uint32_t box_cols, uint32_t box_rows, bool swz) {
    cuuint64_t dims[2] = {cols, rows};
    cuuint64_t strides[1] = {cols * 2};
    cuuint32_t box[2] = {box_cols, box_rows};
    cuuint32_t es[2] = {1, 1};
    fn(m, CU_TENSOR_MAP_DATA_TYPE_BFLOAT16, 2, const_cast<void*>(ptr), dims, strides, box, es, CU_TENSOR_MAP_INTERLEAVE_NONE,
       swz ? CU_TENSOR_MAP_SWIZZLE_128B : CU_TENSOR_MAP_SWIZZLE_NONE, CU_TENSOR_MAP_L2_PROMOTION_L2_128B, CU_TENSOR_MAP_FLOAT_OOB_FILL_NONE);
}

}

extern "C" void kernel_launch(void* const* d_in, const int* in_sizes, int n_in, void* d_out, int out_size) {
    (void)in_sizes; (void)n_in; (void)out_size;
    EncodeFn fn = nullptr;
    cudaDriverEntryPointQueryResult qr;
    cudaGetDriverEntryPoint("cuTensorMapEncodeTiled", reinterpret_cast<void**>(&fn), cudaEnableDefault, &qr);
    void* o_ptr = nullptr;
    cudaGetSymbolAddress(&o_ptr, g_o);
    Maps maps;
    make_map(fn, &maps.xA, d_in[0], DM, SEQ, 64, 128, true);
    make_map(fn, &maps.wA, d_in[1], 3 * DM, DM, 64, 64, true);
    make_map(fn, &maps.woA, d_in[2], DM, DM, 64, 64, true);
    make_map(fn, &maps.xB, d_in[3], DM, SEQ, 64, 128, true);
    make_map(fn, &maps.wB, d_in[4], 3 * DM, DM, 64, 64, true);
    make_map(fn, &maps.woB, d_in[5], DM, DM, 64, 64, true);
    make_map(fn, &maps.oLd, o_ptr, DM, 2 * SEQ, 64, 64, true);
    make_map(fn, &maps.oSt, o_ptr, DM, 2 * SEQ, 56, 64, false);
    make_map(fn, &maps.out, d_out, 2 * DM, SEQ, 112, 64, false);
    maps.pxA = static_cast<const uint8_t*>(d_in[0]); maps.pwA = static_cast<const uint8_t*>(d_in[1]);
    maps.pwoA = static_cast<const uint8_t*>(d_in[2]); maps.pwoB = static_cast<const uint8_t*>(d_in[5]);
    cudaFuncSetAttribute(fused_kernel, cudaFuncAttributeMaxDynamicSharedMemorySize, SMEM_BYTES);
    fused_kernel<<<NCTA + NSPARE, 512, SMEM_BYTES>>>(maps);
}
```

```cpp
#include <cuda.h>
#include <cuda_runtime.h>
#include <cuda_bf16.h>
#include <stdint.h>

namespace {

constexpr int SEQ = 2048, DM = 448;
constexpr int NCTA = 128;

constexpr uint32_t KV_SLOT   = 16384;
constexpr int      KV_SLOTS  = 6;
constexpr uint32_t OFF_KV    = 0;
constexpr uint32_t OFF_A     = 98304;
constexpr uint32_t OFF_B1    = 65536;
constexpr uint32_t B1_STAGE  = 40960;
constexpr uint32_t OFF_QST   = OFF_B1 + 2 * B1_STAGE;
constexpr uint32_t A_STAGE   = 24576;
constexpr uint32_t OFF_PQ    = OFF_A + 73728;
constexpr uint32_t OFF_PK    = OFF_A + 90112;
constexpr uint32_t OFF_AV    = OFF_A + 106496;
constexpr uint32_t OFF_KVB   = OFF_A + 122880;
constexpr uint32_t OFF_OB    = 2 * KV_SLOT;
constexpr uint32_t OFF_OUTB  = OFF_A + 114688;
constexpr uint32_t OFF_BAR   = 229376;
constexpr uint32_t BAR_B1F = OFF_BAR, BAR_B1E = OFF_BAR + 32, BAR_KVF = OFF_BAR + 64, BAR_KVE = OFF_BAR + 112,
                   BAR_AF = OFF_BAR + 160, BAR_AE = OFF_BAR + 184, BAR_OBF = OFF_BAR + 208, BAR_WOB = OFF_BAR + 264,
                   BAR_ADONE = OFF_BAR + 272, BAR_B1D = OFF_BAR + 280, BAR_NRM = OFF_BAR + 288, BAR_PUB = OFF_BAR + 296,
                   BAR_KNR = OFF_BAR + 304, BAR_QST = OFF_BAR + 312, BAR_OST = OFF_BAR + 320, BAR_GO = OFF_BAR + 328,
                   BAR_X1 = OFF_BAR + 336, BAR_Y2 = OFF_BAR + 344, BAR_EPO = OFF_BAR + 352;
constexpr uint32_t OFF_EPOCH = OFF_BAR + 368;
constexpr uint32_t OFF_VBAD  = OFF_BAR + 372;
constexpr uint32_t OFF_LIMIT = OFF_BAR + 376;
constexpr uint32_t OFF_KN    = OFF_BAR + 384;
constexpr uint32_t OFF_QN    = OFF_BAR + 416;
constexpr uint32_t SMEM_BYTES = OFF_BAR + 1024;

constexpr float SAFE_BOUND_SQ = 40.f * 40.f * 0.9f;
constexpr float Q_SCALE = 0.18898223650461362f * 1.4426950408889634f;

__device__ uint4 g_kv[8 * 32 * (KV_SLOT / 16)];
__device__ __nv_bfloat16 g_o[2 * SEQ * DM];
__device__ float4 g_akv[8 * 16 * 4 * 128];
__device__ unsigned long long g_kvflag[8 * 32];
__device__ uint2 g_akv2[8 * 512];
__device__ unsigned int g_akvflag[8], g_akv2flag[8];
__device__ unsigned int g_aoflag[16];
__device__ unsigned int g_boflag[32 * 32];
__device__ unsigned long long g_done;

#define DESC_HI 0x40000040

__device__ __forceinline__ void mma_ss_n184_kn(float (&d)[92], uint32_t alo, uint32_t blo, int scale_d) {
    asm volatile("{\n.reg .pred p;\n.reg .b64 da, db;\nsetp.ne.b32 p, %95, 0;\nmov.b64 da, {%92, %94};\nmov.b64 db, {%93, %94};\n"
        "wgmma.mma_async.sync.aligned.m64n184k16.f32.bf16.bf16 "
        "{%0, %1, %2, %3, %4, %5, %6, %7, %8, %9, %10, %11, %12, %13, %14, %15, "
        "%16, %17, %18, %19, %20, %21, %22, %23, %24, %25, %26, %27, %28, %29, %30, %31, "
        "%32, %33, %34, %35, %36, %37, %38, %39, %40, %41, %42, %43, %44, %45, %46, %47, "
        "%48, %49, %50, %51, %52, %53, %54, %55, %56, %57, %58, %59, %60, %61, %62, %63, "
        "%64, %65, %66, %67, %68, %69, %70, %71, %72, %73, %74, %75, %76, %77, %78, %79, "
        "%80, %81, %82, %83, %84, %85, %86, %87, %88, %89, %90, %91}, "
        "da, db, p, 1, 1, 0, 1;\n}\n"
        : "+f"(d[0]), "+f"(d[1]), "+f"(d[2]), "+f"(d[3]), "+f"(d[4]), "+f"(d[5]), "+f"(d[6]), "+f"(d[7]),
          "+f"(d[8]), "+f"(d[9]), "+f"(d[10]), "+f"(d[11]), "+f"(d[12]), "+f"(d[13]), "+f"(d[14]), "+f"(d[15]),
          "+f"(d[16]), "+f"(d[17]), "+f"(d[18]), "+f"(d[19]), "+f"(d[20]), "+f"(d[21]), "+f"(d[22]), "+f"(d[23]),
          "+f"(d[24]), "+f"(d[25]), "+f"(d[26]), "+f"(d[27]), "+f"(d[28]), "+f"(d[29]), "+f"(d[30]), "+f"(d[31]),
          "+f"(d[32]), "+f"(d[33]), "+f"(d[34]), "+f"(d[35]), "+f"(d[36]), "+f"(d[37]), "+f"(d[38]), "+f"(d[39]),
          "+f"(d[40]), "+f"(d[41]), "+f"(d[42]), "+f"(d[43]), "+f"(d[44]), "+f"(d[45]), "+f"(d[46]), "+f"(d[47]),
          "+f"(d[48]), "+f"(d[49]), "+f"(d[50]), "+f"(d[51]), "+f"(d[52]), "+f"(d[53]), "+f"(d[54]), "+f"(d[55]),
          "+f"(d[56]), "+f"(d[57]), "+f"(d[58]), "+f"(d[59]), "+f"(d[60]), "+f"(d[61]), "+f"(d[62]), "+f"(d[63]),
          "+f"(d[64]), "+f"(d[65]), "+f"(d[66]), "+f"(d[67]), "+f"(d[68]), "+f"(d[69]), "+f"(d[70]), "+f"(d[71]),
          "+f"(d[72]), "+f"(d[73]), "+f"(d[74]), "+f"(d[75]), "+f"(d[76]), "+f"(d[77]), "+f"(d[78]), "+f"(d[79]),
          "+f"(d[80]), "+f"(d[81]), "+f"(d[82]), "+f"(d[83]), "+f"(d[84]), "+f"(d[85]), "+f"(d[86]), "+f"(d[87]),
          "+f"(d[88]), "+f"(d[89]), "+f"(d[90]), "+f"(d[91])
        : "r"(alo), "r"(blo), "n"(DESC_HI), "r"(scale_d));
}
__device__ __forceinline__ void mma_ss_n112_kn(float (&d)[56], uint32_t alo, uint32_t blo, int scale_d) {
    asm volatile("{\n.reg .pred p;\n.reg .b64 da, db;\nsetp.ne.b32 p, %59, 0;\nmov.b64 da, {%56, %58};\nmov.b64 db, {%57, %58};\n"
        "wgmma.mma_async.sync.aligned.m64n112k16.f32.bf16.bf16 "
        "{%0, %1, %2, %3, %4, %5, %6, %7, %8, %9, %10, %11, %12, %13, %14, %15, "
        "%16, %17, %18, %19, %20, %21, %22, %23, %24, %25, %26, %27, %28, %29, %30, %31, "
        "%32, %33, %34, %35, %36, %37, %38, %39, %40, %41, %42, %43, %44, %45, %46, %47, "
        "%48, %49, %50, %51, %52, %53, %54, %55}, "
        "da, db, p, 1, 1, 0, 1;\n}\n"
        : "+f"(d[0]), "+f"(d[1]), "+f"(d[2]), "+f"(d[3]), "+f"(d[4]), "+f"(d[5]), "+f"(d[6]), "+f"(d[7]),
          "+f"(d[8]), "+f"(d[9]), "+f"(d[10]), "+f"(d[11]), "+f"(d[12]), "+f"(d[13]), "+f"(d[14]), "+f"(d[15]),
          "+f"(d[16]), "+f"(d[17]), "+f"(d[18]), "+f"(d[19]), "+f"(d[20]), "+f"(d[21]), "+f"(d[22]), "+f"(d[23]),
          "+f"(d[24]), "+f"(d[25]), "+f"(d[26]), "+f"(d[27]), "+f"(d[28]), "+f"(d[29]), "+f"(d[30]), "+f"(d[31]),
          "+f"(d[32]), "+f"(d[33]), "+f"(d[34]), "+f"(d[35]), "+f"(d[36]), "+f"(d[37]), "+f"(d[38]), "+f"(d[39]),
          "+f"(d[40]), "+f"(d[41]), "+f"(d[42]), "+f"(d[43]), "+f"(d[44]), "+f"(d[45]), "+f"(d[46]), "+f"(d[47]),
          "+f"(d[48]), "+f"(d[49]), "+f"(d[50]), "+f"(d[51]), "+f"(d[52]), "+f"(d[53]), "+f"(d[54]), "+f"(d[55])
        : "r"(alo), "r"(blo), "n"(DESC_HI), "r"(scale_d));
}
__device__ __forceinline__ void mma_ss_n64_kn(float (&d)[32], uint32_t alo, uint32_t blo, int scale_d) {
    asm volatile("{\n.reg .pred p;\n.reg .b64 da, db;\nsetp.ne.b32 p, %35, 0;\nmov.b64 da, {%32, %34};\nmov.b64 db, {%33, %34};\n"
        "wgmma.mma_async.sync.aligned.m64n64k16.f32.bf16.bf16 "
        "{%0, %1, %2, %3, %4, %5, %6, %7, %8, %9, %10, %11, %12, %13, %14, %15, "
        "%16, %17, %18, %19, %20, %21, %22, %23, %24, %25, %26, %27, %28, %29, %30, %31}, "
        "da, db, p, 1, 1, 0, 1;\n}\n"
        : "+f"(d[0]), "+f"(d[1]), "+f"(d[2]), "+f"(d[3]), "+f"(d[4]), "+f"(d[5]), "+f"(d[6]), "+f"(d[7]),
          "+f"(d[8]), "+f"(d[9]), "+f"(d[10]), "+f"(d[11]), "+f"(d[12]), "+f"(d[13]), "+f"(d[14]), "+f"(d[15]),
          "+f"(d[16]), "+f"(d[17]), "+f"(d[18]), "+f"(d[19]), "+f"(d[20]), "+f"(d[21]), "+f"(d[22]), "+f"(d[23]),
          "+f"(d[24]), "+f"(d[25]), "+f"(d[26]), "+f"(d[27]), "+f"(d[28]), "+f"(d[29]), "+f"(d[30]), "+f"(d[31])
        : "r"(alo), "r"(blo), "n"(DESC_HI), "r"(scale_d));
}
__device__ __forceinline__ void mma_ss_n64_mn(float (&d)[32], uint32_t alo, uint32_t blo, int scale_d) {
    asm volatile("{\n.reg .pred p;\n.reg .b64 da, db;\nsetp.ne.b32 p, %35, 0;\nmov.b64 da, {%32, %34};\nmov.b64 db, {%33, %34};\n"
        "wgmma.mma_async.sync.aligned.m64n64k16.f32.bf16.bf16 "
        "{%0, %1, %2, %3, %4, %5, %6, %7, %8, %9, %10, %11, %12, %13, %14, %15, "
        "%16, %17, %18, %19, %20, %21, %22, %23, %24, %25, %26, %27, %28, %29, %30, %31}, "
        "da, db, p, 1, 1, 1, 1;\n}\n"
        : "+f"(d[0]), "+f"(d[1]), "+f"(d[2]), "+f"(d[3]), "+f"(d[4]), "+f"(d[5]), "+f"(d[6]), "+f"(d[7]),
          "+f"(d[8]), "+f"(d[9]), "+f"(d[10]), "+f"(d[11]), "+f"(d[12]), "+f"(d[13]), "+f"(d[14]), "+f"(d[15]),
          "+f"(d[16]), "+f"(d[17]), "+f"(d[18]), "+f"(d[19]), "+f"(d[20]), "+f"(d[21]), "+f"(d[22]), "+f"(d[23]),
          "+f"(d[24]), "+f"(d[25]), "+f"(d[26]), "+f"(d[27]), "+f"(d[28]), "+f"(d[29]), "+f"(d[30]), "+f"(d[31])
        : "r"(alo), "r"(blo), "n"(DESC_HI), "r"(scale_d));
}
__device__ __forceinline__ void mma_rs_n56_n(float (&d)[28], uint32_t a0, uint32_t a1, uint32_t a2, uint32_t a3, uint32_t blo, int scale_d) {
    asm volatile("{\n.reg .pred p;\n.reg .b64 db;\nsetp.ne.b32 p, %34, 0;\nmov.b64 db, {%32, %33};\n"
        "wgmma.mma_async.sync.aligned.m64n56k16.f32.bf16.bf16 "
        "{%0, %1, %2, %3, %4, %5, %6, %7, %8, %9, %10, %11, %12, %13, %14, %15, "
        "%16, %17, %18, %19, %20, %21, %22, %23, %24, %25, %26, %27}, "
        "{%28, %29, %30, %31}, db, p, 1, 1, 1;\n}\n"
        : "+f"(d[0]), "+f"(d[1]), "+f"(d[2]), "+f"(d[3]), "+f"(d[4]), "+f"(d[5]), "+f"(d[6]), "+f"(d[7]),
          "+f"(d[8]), "+f"(d[9]), "+f"(d[10]), "+f"(d[11]), "+f"(d[12]), "+f"(d[13]), "+f"(d[14]), "+f"(d[15]),
          "+f"(d[16]), "+f"(d[17]), "+f"(d[18]), "+f"(d[19]), "+f"(d[20]), "+f"(d[21]), "+f"(d[22]), "+f"(d[23]),
          "+f"(d[24]), "+f"(d[25]), "+f"(d[26]), "+f"(d[27])
        : "r"(a0), "r"(a1), "r"(a2), "r"(a3), "r"(blo), "n"(DESC_HI), "r"(scale_d));
}
__device__ __forceinline__ void mma_rs_n112_n(float (&d)[56], uint32_t a0, uint32_t a1, uint32_t a2, uint32_t a3, uint32_t blo, int scale_d) {
    asm volatile("{\n.reg .pred p;\n.reg .b64 db;\nsetp.ne.b32 p, %62, 0;\nmov.b64 db, {%60, %61};\n"
        "wgmma.mma_async.sync.aligned.m64n112k16.f32.bf16.bf16 "
        "{%0, %1, %2, %3, %4, %5, %6, %7, %8, %9, %10, %11, %12, %13, %14, %15, "
        "%16, %17, %18, %19, %20, %21, %22, %23, %24, %25, %26, %27, %28, %29, %30, %31, "
        "%32, %33, %34, %35, %36, %37, %38, %39, %40, %41, %42, %43, %44, %45, %46, %47, "
        "%48, %49, %50, %51, %52, %53, %54, %55}, "
        "{%56, %57, %58, %59}, db, p, 1, 1, 1;\n}\n"
        : "+f"(d[0]), "+f"(d[1]), "+f"(d[2]), "+f"(d[3]), "+f"(d[4]), "+f"(d[5]), "+f"(d[6]), "+f"(d[7]),
          "+f"(d[8]), "+f"(d[9]), "+f"(d[10]), "+f"(d[11]), "+f"(d[12]), "+f"(d[13]), "+f"(d[14]), "+f"(d[15]),
          "+f"(d[16]), "+f"(d[17]), "+f"(d[18]), "+f"(d[19]), "+f"(d[20]), "+f"(d[21]), "+f"(d[22]), "+f"(d[23]),
          "+f"(d[24]), "+f"(d[25]), "+f"(d[26]), "+f"(d[27]), "+f"(d[28]), "+f"(d[29]), "+f"(d[30]), "+f"(d[31]),
          "+f"(d[32]), "+f"(d[33]), "+f"(d[34]), "+f"(d[35]), "+f"(d[36]), "+f"(d[37]), "+f"(d[38]), "+f"(d[39]),
          "+f"(d[40]), "+f"(d[41]), "+f"(d[42]), "+f"(d[43]), "+f"(d[44]), "+f"(d[45]), "+f"(d[46]), "+f"(d[47]),
          "+f"(d[48]), "+f"(d[49]), "+f"(d[50]), "+f"(d[51]), "+f"(d[52]), "+f"(d[53]), "+f"(d[54]), "+f"(d[55])
        : "r"(a0), "r"(a1), "r"(a2), "r"(a3), "r"(blo), "n"(DESC_HI), "r"(scale_d));
}
__device__ __forceinline__ void mma_rs_n64_k(float (&d)[32], uint32_t a0, uint32_t a1, uint32_t a2, uint32_t a3, uint32_t blo, int scale_d) {
    asm volatile("{\n.reg .pred p;\n.reg .b64 db;\nsetp.ne.b32 p, %38, 0;\nmov.b64 db, {%36, %37};\n"
        "wgmma.mma_async.sync.aligned.m64n64k16.f32.bf16.bf16 "
        "{%0, %1, %2, %3, %4, %5, %6, %7, %8, %9, %10, %11, %12, %13, %14, %15, "
        "%16, %17, %18, %19, %20, %21, %22, %23, %24, %25, %26, %27, %28, %29, %30, %31}, "
        "{%32, %33, %34, %35}, db, p, 1, 1, 0;\n}\n"
        : "+f"(d[0]), "+f"(d[1]), "+f"(d[2]), "+f"(d[3]), "+f"(d[4]), "+f"(d[5]), "+f"(d[6]), "+f"(d[7]),
          "+f"(d[8]), "+f"(d[9]), "+f"(d[10]), "+f"(d[11]), "+f"(d[12]), "+f"(d[13]), "+f"(d[14]), "+f"(d[15]),
          "+f"(d[16]), "+f"(d[17]), "+f"(d[18]), "+f"(d[19]), "+f"(d[20]), "+f"(d[21]), "+f"(d[22]), "+f"(d[23]),
          "+f"(d[24]), "+f"(d[25]), "+f"(d[26]), "+f"(d[27]), "+f"(d[28]), "+f"(d[29]), "+f"(d[30]), "+f"(d[31])
        : "r"(a0), "r"(a1), "r"(a2), "r"(a3), "r"(blo), "n"(DESC_HI), "r"(scale_d));
}
__device__ __forceinline__ void mma_rs_n32_n(float (&d)[16], uint32_t a0, uint32_t a1, uint32_t a2, uint32_t a3, uint32_t blo, int scale_d) {
    asm volatile("{\n.reg .pred p;\n.reg .b64 db;\nsetp.ne.b32 p, %22, 0;\nmov.b64 db, {%20, %21};\n"
        "wgmma.mma_async.sync.aligned.m64n32k16.f32.bf16.bf16 "
        "{%0, %1, %2, %3, %4, %5, %6, %7, %8, %9, %10, %11, %12, %13, %14, %15}, "
        "{%16, %17, %18, %19}, db, p, 1, 1, 1;\n}\n"
        : "+f"(d[0]), "+f"(d[1]), "+f"(d[2]), "+f"(d[3]), "+f"(d[4]), "+f"(d[5]), "+f"(d[6]), "+f"(d[7]),
          "+f"(d[8]), "+f"(d[9]), "+f"(d[10]), "+f"(d[11]), "+f"(d[12]), "+f"(d[13]), "+f"(d[14]), "+f"(d[15])
        : "r"(a0), "r"(a1), "r"(a2), "r"(a3), "r"(blo), "n"(DESC_HI), "r"(scale_d));
}

__device__ __forceinline__ void wg_fence() { asm volatile("wgmma.fence.sync.aligned;" ::: "memory"); }
__device__ __forceinline__ void wg_commit() { asm volatile("wgmma.commit_group.sync.aligned;" ::: "memory"); }
template <int N> __device__ __forceinline__ void wg_wait() { asm volatile("wgmma.wait_group.sync.aligned %0;" ::"n"(N) : "memory"); }
template <int N> __device__ __forceinline__ void pin(float (&d)[N]) {
#pragma unroll
    for (int i = 0; i < N; i++) asm volatile("" : "+f"(d[i])::"memory");
}
template <int N> __device__ __forceinline__ void pin(uint32_t (&d)[N]) {
#pragma unroll
    for (int i = 0; i < N; i++) asm volatile("" : "+r"(d[i])::"memory");
}
__device__ __forceinline__ uint32_t dlo(uint32_t addr, uint32_t lbo = 0) { return ((addr >> 4) & 0x3FFF) | ((lbo >> 4) << 16); }
__device__ __forceinline__ float ex2(float x) { float y; asm("ex2.approx.ftz.f32 %0, %1;" : "=f"(y) : "f"(x)); return y; }
__device__ __forceinline__ float rcp(float x) { float y; asm("rcp.approx.ftz.f32 %0, %1;" : "=f"(y) : "f"(x)); return y; }
__device__ __forceinline__ uint32_t pack(float lo, float hi) { uint32_t r; asm("cvt.rn.bf16x2.f32 %0, %1, %2;" : "=r"(r) : "f"(hi), "f"(lo)); return r; }
__device__ __forceinline__ float bf_lo(uint32_t v) { return __uint_as_float(v << 16); }
__device__ __forceinline__ float bf_hi(uint32_t v) { return __uint_as_float(v & 0xFFFF0000u); }
__device__ __forceinline__ float rbf(float x) { return bf_hi(pack(0.f, x)); }

__device__ __forceinline__ void mbar_init(uint32_t bar, uint32_t cnt) { asm volatile("mbarrier.init.shared::cta.b64 [%0], %1;" ::"r"(bar), "r"(cnt)); }
__device__ __forceinline__ void mbar_expect(uint32_t bar, uint32_t bytes) { asm volatile("mbarrier.arrive.expect_tx.shared::cta.b64 _, [%0], %1;" ::"r"(bar), "r"(bytes) : "memory"); }
__device__ __forceinline__ void mbar_arrive(uint32_t bar) { asm volatile("mbarrier.arrive.shared::cta.b64 _, [%0];" ::"r"(bar) : "memory"); }
__device__ __forceinline__ void mbar_wait(uint32_t bar, uint32_t parity) {
    asm volatile(
        "{\n.reg .pred p;\n.reg .u32 c;\n"
        "mbarrier.try_wait.parity.shared::cta.b64 p, [%0], %1;\n@p bra W_DONE;\nmov.u32 c, 0;\n"
        "W_LOOP:\nmbarrier.try_wait.parity.shared::cta.b64 p, [%0], %1;\n@p bra W_DONE;\n"
        "add.u32 c, c, 1;\nsetp.lt.u32 p, c, 0x400000;\n@p bra W_LOOP;\ntrap;\nW_DONE:\n}\n" ::"r"(bar), "r"(parity) : "memory");
}
__device__ __forceinline__ void mbar_wait_bg(uint32_t bar, uint32_t parity) {
    asm volatile(
        "{\n.reg .pred p;\n.reg .u32 c;\nmov.u32 c, 0;\n"
        "W_LOOP:\nmbarrier.try_wait.parity.shared::cta.b64 p, [%0], %1, 20000;\n@p bra W_DONE;\n"
        "add.u32 c, c, 1;\nsetp.lt.u32 p, c, 0x40000;\n@p bra W_LOOP;\ntrap;\nW_DONE:\n}\n" ::"r"(bar), "r"(parity) : "memory");
}
__device__ __forceinline__ void warp_arrive(uint32_t bar) { if ((threadIdx.x & 31) == 0) mbar_arrive(bar); }
__device__ __forceinline__ void named_sync(int id) { asm volatile("bar.sync %0, 128;" ::"r"(id) : "memory"); }
__device__ __forceinline__ void fence_async() { asm volatile("fence.proxy.async.global;" ::: "memory"); }
__device__ __forceinline__ void fence_async_smem() { asm volatile("fence.proxy.async.shared::cta;" ::: "memory"); }

__device__ __forceinline__ void tma_load(uint32_t dst, const CUtensorMap* m, int c0, int c1, uint32_t bar) {
    asm volatile("cp.async.bulk.tensor.2d.shared::cluster.global.mbarrier::complete_tx::bytes [%0], [%1, {%3, %4}], [%2];"
                 ::"r"(dst), "l"(m), "r"(bar), "r"(c0), "r"(c1) : "memory");
}
__device__ __forceinline__ void tma_load3(uint32_t dst, const CUtensorMap* m, int c0, int c1, int c2, uint32_t bar) {
    asm volatile("cp.async.bulk.tensor.3d.shared::cluster.global.mbarrier::complete_tx::bytes [%0], [%1, {%3, %4, %5}], [%2];"
                 ::"r"(dst), "l"(m), "r"(bar), "r"(c0), "r"(c1), "r"(c2) : "memory");
}
__device__ __forceinline__ void tma_store(const CUtensorMap* m, int c0, int c1, uint32_t src) {
    asm volatile("cp.async.bulk.tensor.2d.global.shared::cta.bulk_group [%0, {%2, %3}], [%1];" ::"l"(m), "r"(src), "r"(c0), "r"(c1) : "memory");
}
__device__ __forceinline__ void bulk_load(uint32_t dst, const void* src, uint32_t bytes, uint32_t bar) {
    asm volatile("cp.async.bulk.shared::cluster.global.mbarrier::complete_tx::bytes [%0], [%1], %2, [%3];" ::"r"(dst), "l"(src), "r"(bytes), "r"(bar) : "memory");
}
__device__ __forceinline__ void bulk_store(void* dst, uint32_t src, uint32_t bytes) {
    asm volatile("cp.async.bulk.global.shared::cta.bulk_group [%0], [%1], %2;" ::"l"(dst), "r"(src), "r"(bytes) : "memory");
}
__device__ __forceinline__ void bulk_commit() { asm volatile("cp.async.bulk.commit_group;" ::: "memory"); }
__device__ __forceinline__ void bulk_wait_all() { asm volatile("cp.async.bulk.wait_group 0;" ::: "memory"); }
__device__ __forceinline__ void bulk_wait_read() { asm volatile("cp.async.bulk.wait_group.read 0;" ::: "memory"); }

__device__ __forceinline__ void red_release(unsigned int* p) { asm volatile("red.release.gpu.global.add.u32 [%0], 1;" ::"l"(p) : "memory"); }
__device__ __forceinline__ void red_after_bulk(unsigned int* p) { asm volatile("red.relaxed.gpu.global.add.u32 [%0], 1;" ::"l"(p) : "memory"); }
__device__ __forceinline__ void fence_acquire() { asm volatile("fence.acquire.gpu;" ::: "memory"); }
__device__ __forceinline__ void wait_count(const unsigned int* p, uint32_t target) {
    for (uint32_t n = 0;; n++) {
        uint32_t v;
        asm volatile("ld.relaxed.gpu.global.u32 %0, [%1];" : "=r"(v) : "l"(p) : "memory");
        if ((int32_t)(v - target) >= 0) break;
        if (n > (1u << 21)) __trap();
    }
    fence_acquire();
}
__device__ __forceinline__ void stsm4(uint32_t addr, uint32_t a, uint32_t b, uint32_t c, uint32_t d) {
    asm volatile("stmatrix.sync.aligned.m8n8.x4.shared.b16 [%0], {%1, %2, %3, %4};" ::"r"(addr), "r"(a), "r"(b), "r"(c), "r"(d) : "memory");
}
__device__ __forceinline__ void load_frags(uint32_t (&f)[16], uint32_t la) {
    const uint32_t lane = threadIdx.x & 31;
#pragma unroll
    for (int s = 0; s < 4; s++)
        asm volatile("ldmatrix.sync.aligned.m8n8.x4.shared.b16 {%0, %1, %2, %3}, [%4];"
                     : "=r"(f[4 * s]), "=r"(f[4 * s + 1]), "=r"(f[4 * s + 2]), "=r"(f[4 * s + 3])
                     : "r"(la + (((s * 2 + (lane >> 4)) ^ (lane & 7)) << 4)) : "memory");
}
__device__ __forceinline__ void stsm2(uint32_t addr, uint32_t a, uint32_t b) {
    asm volatile("stmatrix.sync.aligned.m8n8.x2.shared.b16 [%0], {%1, %2};" ::"r"(addr), "r"(a), "r"(b) : "memory");
}
__device__ __forceinline__ void sts_u(uint32_t addr, uint32_t v) { asm volatile("st.shared.u32 [%0], %1;" ::"r"(addr), "r"(v) : "memory"); }
__device__ __forceinline__ uint32_t lds_u(uint32_t addr) { uint32_t v; asm volatile("ld.shared.u32 %0, [%1];" : "=r"(v) : "r"(addr) : "memory"); return v; }

__device__ __forceinline__ void store_tile16(uint32_t tile, int row0, const uint32_t (&v)[16]) {
    const int lane = threadIdx.x & 31;
    const int row = row0 + (lane & 7) + ((lane >> 3) & 1) * 8;
    const uint32_t base = tile + row * 128;
#pragma unroll
    for (int c = 0; c < 8; c += 2) stsm4(base + (((c + (lane >> 4)) ^ (lane & 7)) << 4), v[2 * c], v[2 * c + 1], v[2 * c + 2], v[2 * c + 3]);
}
__device__ __forceinline__ void spread_pair(const uint32_t (&p)[14], uint32_t (&v)[16], uint32_t pad_lo, uint32_t pad_hi) {
    const bool lo = (threadIdx.x & 2) == 0;
#pragma unroll
    for (int i = 0; i < 6; i++) { v[i] = p[i]; v[10 + i] = p[8 + i]; }
    v[6] = lo ? p[6] : pad_lo; v[7] = lo ? p[7] : pad_lo;
    v[8] = lo ? pad_hi : p[6]; v[9] = lo ? pad_hi : p[7];
}
__device__ __forceinline__ uint4 lds128(uint32_t addr) {
    uint4 v; asm volatile("ld.shared.v4.u32 {%0, %1, %2, %3}, [%4];" : "=r"(v.x), "=r"(v.y), "=r"(v.z), "=r"(v.w) : "r"(addr) : "memory"); return v;
}
__device__ __forceinline__ uint32_t bf2_sq(uint32_t x, uint32_t acc) { uint32_t y; asm("fma.rn.bf16x2 %0, %1, %1, %2;" : "=r"(y) : "r"(x), "r"(acc)); return y; }
__device__ __forceinline__ uint32_t bf2_absmax(uint32_t x, uint32_t acc) { uint32_t y; asm("max.NaN.xorsign.abs.bf16x2 %0, %1, %2;" : "=r"(y) : "r"(x), "r"(acc)); return y; }
__device__ __forceinline__ uint32_t bf2_add(uint32_t a, uint32_t b) { uint32_t y; asm("add.rn.bf16x2 %0, %1, %2;" : "=r"(y) : "r"(a), "r"(b)); return y; }
__device__ __forceinline__ void row_norms(const uint32_t (&ad)[8], uint32_t off, uint32_t& n0, uint32_t& n1) {
    uint4 x[8];
#pragma unroll
    for (int c = 0; c < 8; c++) x[c] = lds128(ad[c] + off);
    uint32_t s[8];
#pragma unroll
    for (int c = 0; c < 8; c++) s[c] = bf2_sq(x[c].w, bf2_sq(x[c].z, bf2_sq(x[c].y, bf2_sq(x[c].x, 0u))));
    const uint32_t a = bf2_add(bf2_add(s[0], s[1]), bf2_add(s[2], s[3])), b = bf2_add(bf2_add(s[4], s[5]), bf2_add(s[6], s[7]));
    n0 = __float_as_uint(bf_lo(a) + bf_hi(a));
    n1 = __float_as_uint(bf_lo(b) + bf_hi(b));
}

template <int N>
__device__ __forceinline__ void cta_norms(uint32_t table, float& n0, float& n1) {
    const uint32_t x = lds_u(table + (threadIdx.x & (2 * N - 1)) * 4);
    n0 = __uint_as_float(__reduce_max_sync(0xffffffffu, (threadIdx.x & 1) ? 0u : x));
    n1 = __uint_as_float(__reduce_max_sync(0xffffffffu, (threadIdx.x & 1) ? x : 0u));
}
__device__ __forceinline__ void lower_limit(uint32_t sb, uint32_t t) { asm volatile("red.shared.min.u32 [%0], %1;" ::"r"(sb + OFF_LIMIT), "r"(t) : "memory"); }

__device__ __forceinline__ void qk(float (&S)[32], const uint32_t (&Q)[8], uint32_t klo) {
    mma_rs_n64_k(S, Q[0], Q[1], Q[2], Q[3], klo, 0);
    mma_rs_n64_k(S, Q[4], Q[5], Q[6], Q[7], klo + 2, 1);
}
__device__ __forceinline__ void pv(float (&O)[16], const uint32_t (&P)[16], uint32_t vlo) {
#pragma unroll
    for (int s = 0; s < 4; s++) mma_rs_n32_n(O, P[4 * s], P[4 * s + 1], P[4 * s + 2], P[4 * s + 3], vlo + s * 128, 1);
}
template <bool SAFE>
__device__ __forceinline__ void softmax_tile(float (&S)[32], uint32_t (&P)[16], float (&O)[16], float (&m)[2]) {
    if (SAFE) {
#pragma unroll
        for (int j = 0; j < 16; j++) P[j] = pack(ex2(S[2 * j]), ex2(S[2 * j + 1]));
    } else {
        float m0 = m[0], m1 = m[1];
#pragma unroll
        for (int j = 0; j < 8; j++) { m0 = fmaxf(m0, fmaxf(S[4 * j], S[4 * j + 1])); m1 = fmaxf(m1, fmaxf(S[4 * j + 2], S[4 * j + 3])); }
        m0 = fmaxf(m0, __shfl_xor_sync(0xffffffffu, m0, 1)); m1 = fmaxf(m1, __shfl_xor_sync(0xffffffffu, m1, 1));
        m0 = fmaxf(m0, __shfl_xor_sync(0xffffffffu, m0, 2)); m1 = fmaxf(m1, __shfl_xor_sync(0xffffffffu, m1, 2));
        const float s0 = ex2(m[0] - m0), s1 = ex2(m[1] - m1);
        m[0] = m0; m[1] = m1;
#pragma unroll
        for (int j = 0; j < 4; j++) { O[4 * j] *= s0; O[4 * j + 1] *= s0; O[4 * j + 2] *= s1; O[4 * j + 3] *= s1; }
#pragma unroll
        for (int j = 0; j < 8; j++) {
            P[2 * j] = pack(ex2(S[4 * j] - m0), ex2(S[4 * j + 1] - m0));
            P[2 * j + 1] = pack(ex2(S[4 * j + 2] - m1), ex2(S[4 * j + 3] - m1));
        }
    }
}

struct Att {
    float S0[32], S1[32], O0[16], O1[16], m0[2], m1[2];
    uint32_t P0[16], P1[16], Q0[8], Q1[8];
    uint32_t sb, kb;
    bool lead;

    template <int SLOT, int MODE>
    __device__ __forceinline__ uint32_t step_safe(uint32_t npar) {
        constexpr int NS = (SLOT + 1) % KV_SLOTS, PS = (SLOT + KV_SLOTS - 1) % KV_SLOTS;
        const uint32_t kc = kb + SLOT * 1024, kn = kb + NS * 1024, vp = kb + PS * 1024 + 512;
        uint32_t limit = 32;
        wg_fence(); qk(S1, Q1, kc + 4); wg_commit();
        wg_wait<1>(); pin(O0); pin(P0);
        pv(O1, P1, vp + 4); wg_commit();
        softmax_tile<true>(S0, P0, O0, m0);
        pin(P0);
        if (MODE != 2) {
            mbar_wait(sb + BAR_KVF + NS * 8, npar);
            if (MODE == 0) limit = lds_u(sb + OFF_LIMIT);
            wg_wait<1>(); pin(S1);
            wg_fence(); qk(S0, Q0, kn); wg_commit();
            wg_wait<1>(); pin(O1); pin(P1);
            if (lead) mbar_arrive(sb + BAR_KVE + PS * 8);
            pv(O0, P0, kc + 512); wg_commit();
            softmax_tile<true>(S1, P1, O1, m1);
            pin(P1);
            if (SLOT == 1) { wg_wait<0>(); pin(O0); } else wg_wait<1>();
            pin(S0);
        } else {
            mbar_wait(sb + BAR_NRM, 0);
            const bool keep = lds_u(sb + OFF_LIMIT) == 0;
            wg_wait<0>(); pin(S1); pin(O1); pin(P1);
            if (lead && !keep) mbar_arrive(sb + BAR_KVE + PS * 8);
            wg_fence(); pv(O0, P0, kc + 512); wg_commit();
            softmax_tile<true>(S1, P1, O1, m1);
            pin(P1);
            mbar_wait(sb + BAR_KVF + NS * 8, npar);
            limit = lds_u(sb + OFF_LIMIT);
            wg_fence(); qk(S0, Q0, kn); wg_commit();
            wg_wait<0>(); pin(S0); pin(O0);
        }
        return limit;
    }
    __device__ __forceinline__ void step_max(int slot, int nslot, int pslot, uint32_t npar, bool release) {
        const uint32_t kc = kb + slot * 1024, kn = kb + nslot * 1024, vp = kb + pslot * 1024 + 512;
        wg_fence(); pv(O1, P1, vp + 4); qk(S1, Q1, kc + 4); wg_commit();
        softmax_tile<false>(S0, P0, O0, m0);
        pin(P0); pin(O0);
        mbar_wait(sb + BAR_KVF + nslot * 8, npar);
        wg_wait<0>(); pin(S1); pin(O1);
        wg_fence(); pv(O0, P0, kc + 512); qk(S0, Q0, kn); wg_commit();
        if (lead && release) mbar_arrive(sb + BAR_KVE + pslot * 8);
        softmax_tile<false>(S1, P1, O1, m1);
        pin(P1); pin(O1);
        wg_wait<0>(); pin(S0); pin(O0);
    }
};

__device__ __forceinline__ uint32_t phi2(float a, float b) {
    uint32_t e = pack(ex2(a * 1.4426950408889634f), ex2(b * 1.4426950408889634f)), p;
    asm("min.NaN.bf16x2 %0, %0, %1;" : "+r"(e) : "r"(0x3F803F80u));
    asm("cvt.rn.relu.bf16x2.f32 %0, %1, %2;" : "=r"(p) : "f"(b), "f"(a));
    return bf2_add(bf2_add(p, e), 0x35863586u);
}

__device__ __forceinline__ void store_out(const float (&acc)[56], uint32_t stage, const CUtensorMap* map, int col, int row) {
    const int lane = threadIdx.x & 31, w = (threadIdx.x >> 5) & 3;
    const uint32_t base = stage + (w * 16 + (lane & 7) + ((lane >> 3) & 1) * 8) * 224 + (lane >> 4) * 16;
#pragma unroll
    for (int c = 0; c < 14; c += 2)
        stsm4(base + c * 16, pack(acc[4 * c], acc[4 * c + 1]), pack(acc[4 * c + 2], acc[4 * c + 3]),
              pack(acc[4 * c + 4], acc[4 * c + 5]), pack(acc[4 * c + 6], acc[4 * c + 7]));
    fence_async_smem();
    named_sync(3);
    if ((threadIdx.x & 127) == 0) { tma_store(map, col, row, stage); bulk_commit(); bulk_wait_read(); }
}
__device__ __forceinline__ void store_pair112(uint32_t stage, int row0, const uint32_t (&p)[14]) {
    const int lane = threadIdx.x & 31;
    const uint32_t base = stage + (row0 + (lane & 7) + ((lane >> 3) & 1) * 8) * 112;
    const uint32_t b4 = base + (lane >> 4) * 16;
    stsm4(b4, p[0], p[1], p[2], p[3]);
    stsm4(b4 + 32, p[4], p[5], p[6], p[7]);
    stsm4(b4 + 64, p[8], p[9], p[10], p[11]);
    stsm2(base + 96, p[12], p[13]);
}

struct Maps {
    CUtensorMap xA, wA, woA, xB, wB, woB, oLd, oSt, out;
};

__global__ void __launch_bounds__(512, 1) fused_kernel(const __grid_constant__ Maps maps) {
    extern __shared__ __align__(1024) uint8_t smem_raw[];
    const uint32_t sb = (uint32_t)__cvta_generic_to_shared(smem_raw);
    const int tid = threadIdx.x;
    const int wg = __shfl_sync(0xffffffffu, tid >> 7, 0);
    const int bid = blockIdx.x;
    const int r = bid >> 3, hp = bid & 7;
    const int half = hp >> 2, cq = hp & 3;

    const int wcol = hp * 56 - (hp & 1) * 8;
    const uint32_t wsh = hp & 1;
    auto b1_issue = [&](int kb) {
        const uint32_t st = sb + OFF_B1 + (kb & 3) * B1_STAGE, bar = sb + BAR_B1F + (kb & 3) * 8;
        mbar_expect(bar, B1_STAGE);
        tma_load(st, &maps.xB, kb * 64, r * 128, bar);
        tma_load3(st + 16384, &maps.wB, wcol, kb * 64, 0, bar);
    };

    if ((tid >> 5) == 12) {
        if (tid == 384) {
            if (sb & 1023) __trap();
#pragma unroll
            for (int i = 0; i < 4; i++) mbar_init(sb + BAR_B1F + i * 8, 1);
            fence_async_smem();
            b1_issue(0);
        }
        __syncwarp();
        asm volatile("bar.arrive 0, 512;" ::: "memory");
    } else {
        if (tid == 448) {
            asm volatile("prefetch.tensormap [%0];" ::"l"(&maps.wB) : "memory");
            asm volatile("prefetch.tensormap [%0];" ::"l"(&maps.xB) : "memory");
        }
        if (tid == 416) {
#pragma unroll
            for (int i = 0; i < 3; i++) mbar_init(sb + BAR_B1E + i * 8, 8);
#pragma unroll
            for (int i = 0; i < KV_SLOTS; i++) { mbar_init(sb + BAR_KVF + i * 8, 1); mbar_init(sb + BAR_KVE + i * 8, 8); }
#pragma unroll
            for (int i = 0; i < 3; i++) { mbar_init(sb + BAR_AF + i * 8, 1); mbar_init(sb + BAR_AE + i * 8, 4); }
#pragma unroll
            for (int i = 0; i < 7; i++) mbar_init(sb + BAR_OBF + i * 8, 1);
            mbar_init(sb + BAR_WOB, 1); mbar_init(sb + BAR_ADONE, 1); mbar_init(sb + BAR_B1D, 8);
            mbar_init(sb + BAR_NRM, 4); mbar_init(sb + BAR_PUB, 1); mbar_init(sb + BAR_KNR, 4); mbar_init(sb + BAR_QST, 8);
            mbar_init(sb + BAR_GO, 1); mbar_init(sb + BAR_X1, 1); mbar_init(sb + BAR_Y2, 1); mbar_init(sb + BAR_OST, 2);
            mbar_init(sb + BAR_EPO, 1);
            sts_u(sb + OFF_VBAD, 0); sts_u(sb + OFF_LIMIT, 32);
            fence_async_smem();
        }
        if ((tid >> 5) == 13) { __syncwarp(); asm volatile("bar.arrive 4, 64;" ::: "memory"); }
        asm volatile("bar.sync 0, 512;" ::: "memory");
    }

    if (wg < 2) {
        asm volatile("setmaxnreg.inc.sync.aligned.u32 176;");
        const int lane = tid & 31, w = (tid >> 5) & 3;
        Att a;
        a.sb = sb; a.kb = dlo(sb + OFF_KV); a.lead = lane == 0;
        {
            float acc[92];
#pragma unroll 1
            for (int kb = 0; kb < 7; kb++) {
                const uint32_t st = sb + OFF_B1 + (kb & 3) * B1_STAGE;
                mbar_wait(sb + BAR_B1F + (kb & 3) * 8, kb >> 2);
                const uint32_t da = dlo(st + wg * 8192), db = dlo(st + 16384, 8192) + wsh;
                wg_fence();
#pragma unroll
                for (int ks = 0; ks < 4; ks++) mma_ss_n184_kn(acc, da + ks * 2, db + ks * 128, (kb | ks) != 0);
                wg_commit();
                if (kb > 0) { wg_wait<1>(); if (kb < 4) warp_arrive(sb + BAR_B1E + (kb - 1) * 8); }
            }
#pragma unroll
            for (int i = 0; i < 16; i++) { a.O0[i] = 0.f; a.O1[i] = 0.f; a.P1[i] = 0u; }
            wg_wait<0>(); pin(acc);
            pin(a.O0); pin(a.O1); pin(a.P1);
            warp_arrive(sb + BAR_B1D);
            uint32_t p[14], v[16];
#pragma unroll
            for (int i = 0; i < 14; i++) p[i] = pack(acc[32 + 2 * i], acc[33 + 2 * i]);
            spread_pair(p, v, 0u, 0u);
            store_tile16(sb + OFF_KV + wg * KV_SLOT, w * 16, v);
#pragma unroll
            for (int i = 0; i < 14; i++) p[i] = pack(acc[64 + 2 * i], acc[65 + 2 * i]);
            spread_pair(p, v, (lane & 3) == 2 ? 0x3F80u : 0u, (lane & 3) == 0 ? 0x3F80u : 0u);
            store_tile16(sb + OFF_KV + wg * KV_SLOT + 8192, w * 16, v);
            {
                uint32_t m[7];
#pragma unroll
                for (int i = 0; i < 7; i++) m[i] = bf2_absmax(p[2 * i], p[2 * i + 1]);
                const uint32_t vm = bf2_absmax(bf2_absmax(bf2_absmax(m[0], m[1]), bf2_absmax(m[2], m[3])), bf2_absmax(bf2_absmax(m[4], m[5]), m[6]));
                if ((vm & 0x7FFFu) > 0x5D00u || (vm & 0x7FFF0000u) > 0x5D000000u) sts_u(sb + OFF_VBAD, 1);
            }
            fence_async_smem();
            named_sync(1 + wg);
            if ((tid & 127) == 0) mbar_arrive(sb + BAR_KVF + wg * 8);
#pragma unroll
            for (int i = 0; i < 14; i++) p[i] = pack(acc[2 * i] * Q_SCALE, acc[2 * i + 1] * Q_SCALE);
            spread_pair(p, v, 0u, 0u);
#pragma unroll
            for (int i = 0; i < 8; i++) { a.Q0[i] = v[i]; a.Q1[i] = v[8 + i]; }
            pin(a.Q0); pin(a.Q1);
            mbar_wait(sb + BAR_KVF, 0);
            wg_fence(); qk(a.S0, a.Q0, a.kb); wg_commit();
            store_tile16(sb + OFF_QST + wg * 8192, w * 16, v);
            __syncwarp();
            if (lane == 0) mbar_arrive(sb + BAR_QST);
        }
        wg_wait<0>(); pin(a.S0);
        uint32_t t = 0;
#define SAFE_STEP(S, M, P) { const uint32_t lim = a.step_safe<S, M>(P); if (++t >= lim) { wg_wait<0>(); pin(a.O0); break; } }
        do {
            SAFE_STEP(0, 1, 0)
            SAFE_STEP(1, 2, 0)
            uint32_t par = 0;
#pragma unroll 1
            for (;;) {
                SAFE_STEP(2, 0, par) SAFE_STEP(3, 0, par) SAFE_STEP(4, 0, par)
                par ^= 1;
                SAFE_STEP(5, 0, par) SAFE_STEP(0, 0, par) SAFE_STEP(1, 0, par)
            }
        } while (0);
        if (t < 32) {
            float m_init = 0.f;
            const bool redo = lds_u(sb + OFF_LIMIT) == 0;
            if (redo) {
                m_init = __int_as_float(0xff800000);
                t = 0;
#pragma unroll
                for (int i = 0; i < 16; i++) { a.O0[i] = 0.f; a.O1[i] = 0.f; a.P1[i] = 0u; }
                pin(a.O0); pin(a.O1); pin(a.P1);
                wg_fence(); qk(a.S0, a.Q0, a.kb); wg_commit(); wg_wait<0>(); pin(a.S0);
            }
            a.m0[0] = a.m0[1] = a.m1[0] = a.m1[1] = m_init;
#pragma unroll 1
            for (; t < 32; t++) a.step_max(t % 6, (t + 1) % 6, (t + 5) % 6, ((t + 1) / 6) & 1, t > 0);
        }
        wg_fence(); pv(a.O1, a.P1, a.kb + 1 * 1024 + 512 + 4); wg_commit();
        {
            const int q0 = lane & ~3;
            const bool lo = (lane & 2) == 0;
            uint32_t p[14];
            const float i00 = rcp(__shfl_sync(0xffffffffu, a.O0[12], q0 | 2)), i01 = rcp(__shfl_sync(0xffffffffu, a.O0[14], q0 | 2));
#pragma unroll
            for (int j = 0; j < 3; j++) {
                p[2 * j] = pack(a.O0[4 * j] * i00, a.O0[4 * j + 1] * i00);
                p[2 * j + 1] = pack(a.O0[4 * j + 2] * i01, a.O0[4 * j + 3] * i01);
            }
            p[6] = pack(a.O0[12] * i00, a.O0[13] * i00);
            p[7] = pack(a.O0[14] * i01, a.O0[15] * i01);
            const uint32_t stage = sb + OFF_OUTB + wg * 7168;
            mbar_wait(sb + BAR_ADONE, 0);
            wg_wait<0>(); pin(a.O1);
            const float i10 = rcp(__shfl_sync(0xffffffffu, a.O1[0], q0)), i11 = rcp(__shfl_sync(0xffffffffu, a.O1[2], q0));
#pragma unroll
            for (int j = 0; j < 3; j++) {
                p[8 + 2 * j] = pack(a.O1[4 * j + 4] * i10, a.O1[4 * j + 5] * i10);
                p[9 + 2 * j] = pack(a.O1[4 * j + 6] * i11, a.O1[4 * j + 7] * i11);
            }
            if (!lo) { p[6] = pack(a.O1[0] * i10, a.O1[1] * i10); p[7] = pack(a.O1[2] * i11, a.O1[3] * i11); }
            store_pair112(stage, w * 16, p);
            fence_async_smem();
            named_sync(1 + wg);
            if ((tid & 127) == 0) {
                tma_store(&maps.oSt, hp * 56, SEQ + r * 128 + wg * 64, stage);
                bulk_commit(); bulk_wait_all();
                red_after_bulk(&g_boflag[(r * 2 + wg) * 32]);
                mbar_arrive(sb + BAR_OST);
            }
        }
    } else if (wg == 2) {
        asm volatile("setmaxnreg.dec.sync.aligned.u32 120;");
        const int lane = tid & 31, w = (tid >> 5) & 3, t128 = tid & 127;
        {
            uint32_t ad[8];
#pragma unroll
            for (int c = 0; c < 8; c++) ad[c] = sb + (t128 & 63) * 128 + ((c ^ (t128 & 7)) << 4);
            const uint32_t koff = OFF_KV + (t128 >> 6) * KV_SLOT, qoff = OFF_QST + (t128 >> 6) * 8192;
            pin(ad);
            uint32_t n0, n1;
            mbar_wait(sb + BAR_KVF + (t128 >> 6) * 8, 0);
            row_norms(ad, koff, n0, n1);
            if (lds_u(sb + OFF_VBAD) != 0) n0 = n1 = 0x7f800000u;
            n0 = __reduce_max_sync(0xffffffffu, n0); n1 = __reduce_max_sync(0xffffffffu, n1);
            if (lane == 0) { sts_u(sb + OFF_KN + w * 8, n0); sts_u(sb + OFF_KN + w * 8 + 4, n1); mbar_arrive(sb + BAR_KNR); }
            mbar_wait(sb + BAR_QST, 0);
            row_norms(ad, qoff, n0, n1);
            n0 = __reduce_max_sync(0xffffffffu, n0); n1 = __reduce_max_sync(0xffffffffu, n1);
            mbar_wait(sb + BAR_KNR, 0);
            float k0, k1;
            cta_norms<4>(sb + OFF_KN, k0, k1);
            if (lane == 0) {
                sts_u(sb + OFF_QN + w * 8, n0); sts_u(sb + OFF_QN + w * 8 + 4, n1);
                if (!(__uint_as_float(n0) * k0 <= SAFE_BOUND_SQ && __uint_as_float(n1) * k1 <= SAFE_BOUND_SQ)) lower_limit(sb, 0);
                mbar_arrive(sb + BAR_NRM);
            }
        }
        int st = 0; uint32_t par = 0;
        const uint32_t frow = (w * 16 + (lane & 15)) * 128;
#pragma unroll 1
        for (int part = 0; part < 3; part++) {
            float acc0[28], acc1[28];
#pragma unroll 1
            for (int kb = 0; kb < 7; kb++) {
                const uint32_t base = sb + OFF_A + st * A_STAGE;
                mbar_wait_bg(sb + BAR_AF + st * 8, par);
                const uint32_t db = dlo(base + 16384) + wsh;
                uint32_t f0[16], f1[16];
                load_frags(f0, base + frow); load_frags(f1, base + 8192 + frow);
                pin(f0);
                wg_fence();
#pragma unroll
                for (int ks = 0; ks < 4; ks++) mma_rs_n56_n(acc0, f0[4 * ks], f0[4 * ks + 1], f0[4 * ks + 2], f0[4 * ks + 3], db + ks * 128, (kb | ks) != 0);
                pin(f1);
                wg_fence();
#pragma unroll
                for (int ks = 0; ks < 4; ks++) mma_rs_n56_n(acc1, f1[4 * ks], f1[4 * ks + 1], f1[4 * ks + 2], f1[4 * ks + 3], db + ks * 128, (kb | ks) != 0);
                wg_commit(); wg_wait<0>();
                warp_arrive(sb + BAR_AE + st * 8);
                if (++st == 3) { st = 0; par ^= 1; }
            }
            pin(acc0); pin(acc1);
            const bool is_v = (part == 1);
            const uint32_t tile = sb + (part == 0 ? OFF_PK : is_v ? OFF_AV : OFF_PQ);
            const uint32_t pad_lo = (is_v && (lane & 3) == 2) ? 0x3F80u : 0u, pad_hi = (is_v && (lane & 3) == 0) ? 0x3F80u : 0u;
            uint32_t p[14], p2[14], v[16];
            if (is_v) {
#pragma unroll
                for (int i = 0; i < 14; i++) { p[i] = pack(acc0[2 * i], acc0[2 * i + 1]); p2[i] = pack(acc1[2 * i], acc1[2 * i + 1]); }
            } else {
#pragma unroll
                for (int i = 0; i < 14; i++) p[i] = phi2(acc0[2 * i], acc0[2 * i + 1]);
#pragma unroll
                for (int i = 0; i < 14; i++) p2[i] = phi2(acc1[2 * i], acc1[2 * i + 1]);
            }
            spread_pair(p, v, pad_lo, pad_hi);
            store_tile16(tile, w * 16, v);
            spread_pair(p2, v, pad_lo, pad_hi);
            store_tile16(tile, 64 + w * 16, v);
            if (is_v) {
                fence_async_smem();
                named_sync(3);
                float d[32];
                const uint32_t da = dlo(sb + OFF_PK), db = dlo(sb + OFF_AV);
                wg_fence();
#pragma unroll
                for (int ks = 0; ks < 8; ks++) mma_ss_n64_mn(d, da + ks * 128, db + ks * 128, ks != 0);
                wg_commit(); wg_wait<0>(); pin(d);
#pragma unroll
                for (int i = 0; i < 4; i++)
                    asm volatile("st.shared.v4.f32 [%0], {%1, %2, %3, %4};" ::"r"(sb + OFF_KVB + i * 2048 + t128 * 16),
                                 "f"(w < 2 ? d[4 * i] : d[16 + 4 * i]), "f"(w < 2 ? d[4 * i + 1] : d[17 + 4 * i]),
                                 "f"(w < 2 ? d[4 * i + 2] : d[18 + 4 * i]), "f"(w < 2 ? d[4 * i + 3] : d[19 + 4 * i]) : "memory");
                fence_async_smem();
                named_sync(3);
                if (t128 == 0) { mbar_arrive(sb + BAR_X1); }
            }
        }
        mbar_wait_bg(sb + BAR_Y2, 0);
        {
            uint32_t v[16];
#pragma unroll
            for (int i = 0; i < 4; i++) {
                uint2 x;
                asm volatile("ld.shared.v2.u32 {%0, %1}, [%2];" : "=r"(x.x), "=r"(x.y) : "r"(sb + OFF_AV + i * 1024 + t128 * 8) : "memory");
                v[2 * i] = w < 2 ? x.x : 0u; v[2 * i + 1] = w < 2 ? x.y : 0u;
                v[8 + 2 * i] = w < 2 ? 0u : x.x; v[9 + 2 * i] = w < 2 ? 0u : x.y;
            }
            store_tile16(sb + OFF_KVB, w * 16, v);
        }
        fence_async_smem();
        named_sync(3);
        {
            float n0[32], n1[32];
            const uint32_t da = dlo(sb + OFF_PQ), db = dlo(sb + OFF_KVB);
            wg_fence();
#pragma unroll
            for (int ks = 0; ks < 4; ks++) {
                mma_ss_n64_kn(n0, da + ks * 2, db + ks * 128, ks != 0);
                mma_ss_n64_kn(n1, da + 512 + ks * 2, db + ks * 128, ks != 0);
            }
            wg_commit(); wg_wait<0>(); pin(n0); pin(n1);
            const int q0 = lane & ~3;
            const bool lo = (lane & 2) == 0;
            auto finish = [&](const float (&n)[32], int row0) {
                const float i00 = rcp(rbf(rbf(__shfl_sync(0xffffffffu, n[12], q0 | 2)) + 1e-6f));
                const float i01 = rcp(rbf(rbf(__shfl_sync(0xffffffffu, n[14], q0 | 2)) + 1e-6f));
                const float i10 = rcp(rbf(rbf(__shfl_sync(0xffffffffu, n[16], q0)) + 1e-6f));
                const float i11 = rcp(rbf(rbf(__shfl_sync(0xffffffffu, n[18], q0)) + 1e-6f));
                auto sc = [](float a, float b, float inv) { return pack(a * inv, b * inv); };
                uint32_t p[14];
#pragma unroll
                for (int j = 0; j < 3; j++) {
                    p[2 * j] = sc(n[4 * j], n[4 * j + 1], i00);
                    p[2 * j + 1] = sc(n[4 * j + 2], n[4 * j + 3], i01);
                    p[8 + 2 * j] = sc(n[20 + 4 * j], n[21 + 4 * j], i10);
                    p[9 + 2 * j] = sc(n[22 + 4 * j], n[23 + 4 * j], i11);
                }
                p[6] = sc(lo ? n[12] : n[16], lo ? n[13] : n[17], lo ? i00 : i10);
                p[7] = sc(lo ? n[14] : n[18], lo ? n[15] : n[19], lo ? i01 : i11);
                store_pair112(sb + OFF_PK, row0, p);
            };
            finish(n0, w * 16);
            finish(n1, 64 + w * 16);
            fence_async_smem();
            named_sync(3);
            if (t128 == 0) {
                tma_store(&maps.oSt, hp * 56, r * 128, sb + OFF_PK);
                tma_store(&maps.oSt, hp * 56, r * 128 + 64, sb + OFF_PK + 64 * 112);
                bulk_commit(); bulk_wait_all();
                red_after_bulk(&g_aoflag[r]);
            }
        }
        {
            float acc[56];
#pragma unroll 1
            for (int kb = 0; kb < 7; kb++) {
                const uint32_t base = sb + OFF_A + st * A_STAGE;
                mbar_wait_bg(sb + BAR_AF + st * 8, par);
                const uint32_t db = dlo(base + 8192, 8192);
                uint32_t f0[16];
                load_frags(f0, base + frow);
                pin(f0);
                wg_fence();
#pragma unroll
                for (int ks = 0; ks < 4; ks++) mma_rs_n112_n(acc, f0[4 * ks], f0[4 * ks + 1], f0[4 * ks + 2], f0[4 * ks + 3], db + ks * 128, (kb | ks) != 0);
                wg_commit(); wg_wait<0>();
                if (++st == 3) { st = 0; par ^= 1; }
                if (kb < 4) warp_arrive(sb + BAR_AE + (st == 0 ? 2 : st - 1) * 8);
            }
            pin(acc);
            store_out(acc, sb + OFF_AV, &maps.out, cq * 112, r * 128 + half * 64);
            if (t128 == 0) { mbar_arrive(sb + BAR_ADONE); }
        }
        {
            float acc[56];
            mbar_wait_bg(sb + BAR_WOB, 0);
#pragma unroll 1
            for (int kb = 0; kb < 7; kb++) {
                mbar_wait(sb + BAR_OBF + kb * 8, 0);
                const uint32_t da = dlo(sb + OFF_OB + kb * 8192), db = dlo(sb + OFF_A + kb * 16384, 8192);
                wg_fence();
#pragma unroll
                for (int ks = 0; ks < 4; ks++) mma_ss_n112_kn(acc, da + ks * 2, db + ks * 128, (kb | ks) != 0);
                wg_commit();
            }
            mbar_wait(sb + BAR_OST, 0);
            if (t128 == 32) atomicAdd(&g_done, 1ull);
            wg_wait<0>(); pin(acc);
            store_out(acc, sb + OFF_OUTB, &maps.out, DM + cq * 112, r * 128 + half * 64);
        }
    } else {
        asm volatile("setmaxnreg.dec.sync.aligned.u32 40;");
        if ((tid >> 5) == 12) {
            const int lane = tid & 31;
            const uint8_t* kvg = reinterpret_cast<const uint8_t*>(g_kv) + (size_t)hp * 32 * KV_SLOT;
            unsigned long long* flags = g_kvflag + hp * 32;
            unsigned long long done0 = 0;
            if (lane == 0) {
                asm volatile("ld.relaxed.gpu.global.u64 %0, [%1];" : "=l"(done0) : "l"(&g_done) : "memory");
#pragma unroll 1
                for (int kb = 1; kb < 4; kb++) b1_issue(kb);
            }
            __syncwarp();
            asm volatile("bar.sync 4, 64;" ::: "memory");
            if (lane == 0) {
                const uint32_t e1 = (uint32_t)(done0 / NCTA) + 1;
                sts_u(sb + OFF_EPOCH, e1);
                mbar_arrive(sb + BAR_EPO);
#pragma unroll 1
                for (int kb = 4; kb < 7; kb++) {
                    mbar_wait_bg(sb + BAR_B1E + (kb & 3) * 8, 0);
                    b1_issue(kb);
                }
                unsigned long long dst0 = (unsigned long long)(kvg + (size_t)r * KV_SLOT);
                asm volatile("" : "+l"(dst0));
                mbar_wait(sb + BAR_KVF, 0);
                bulk_store((void*)dst0, sb + OFF_KV, KV_SLOT);
                bulk_commit();
                mbar_wait(sb + BAR_KNR, 0);
                uint32_t k0 = 0, k1 = 0;
#pragma unroll
                for (int i = 0; i < 4; i++) { k0 = max(k0, lds_u(sb + OFF_KN + i * 8)); k1 = max(k1, lds_u(sb + OFF_KN + i * 8 + 4)); }
                const uint32_t nb = (min(k0 + 0xFFFFu, 0x7FFFFFFFu) >> 16) | (min(k1 + 0xFFFFu, 0x7FFFFFFFu) & 0xFFFF0000u);
                const unsigned long long val = ((unsigned long long)e1 << 32) | nb;
                bulk_wait_all();
                asm volatile("st.relaxed.gpu.global.u64 [%0], %1;" ::"l"(flags + r), "l"(val) : "memory");
                mbar_wait_bg(sb + BAR_GO, 0);
                bulk_store(const_cast<uint8_t*>(kvg) + (size_t)(16 + r) * KV_SLOT, sb + OFF_KV + KV_SLOT, KV_SLOT);
                bulk_commit();
                bulk_wait_all();
                asm volatile("st.relaxed.gpu.global.u64 [%0], %1;" ::"l"(flags + 16 + r), "l"(val) : "memory");
                mbar_arrive(sb + BAR_PUB);
            }
        } else if ((tid >> 5) == 14) {
            const int lane = tid & 31;
            const uint8_t* kvg = reinterpret_cast<const uint8_t*>(g_kv) + (size_t)hp * 32 * KV_SLOT;
            const unsigned long long* flags = g_kvflag + hp * 32;
            mbar_wait_bg(sb + BAR_EPO, 0);
            mbar_wait_bg(sb + BAR_B1E + 2 * 8, 0);
            const uint32_t e1 = lds_u(sb + OFF_EPOCH);
            uint32_t todo = ~((1u << r) | (1u << (16 + r))), ready = 0, nb = 0;
            auto ld_flag = [&]() {
                unsigned long long v;
                asm volatile("ld.relaxed.gpu.global.u64 %0, [%1];" : "=l"(v) : "l"(flags + lane) : "memory");
                return v;
            };
            auto seen = [&](unsigned long long v) {
                nb = (uint32_t)v;
                ready = __ballot_sync(0xffffffffu, (uint32_t)(v >> 32) == e1);
                return (ready & todo) != 0;
            };
            auto poll_some = [&]() {
                for (uint32_t n = 0; !seen(ld_flag()); n++) if (n > (1u << 21)) __trap();
                fence_acquire();
                fence_async();
            };
            auto load_tile = [&](int slot, int tile) {
                asm volatile("mbarrier.expect_tx.relaxed.cta.shared::cta.b64 [%0], %1;" ::"r"(sb + BAR_KVF + slot * 8), "r"(KV_SLOT) : "memory");
                bulk_load(sb + OFF_KV + slot * KV_SLOT, kvg + (size_t)tile * KV_SLOT, KV_SLOT, sb + BAR_KVF + slot * 8);
            };
            uint32_t mine = 0;
            int t = 2, armed = 2;
            bool have_q = false;
            float q0 = 0.f, q1 = 0.f;
            auto arm = [&]() {
                if (lane >= armed && lane < t) {
                    if (!(q0 * bf_lo(mine) <= SAFE_BOUND_SQ && q1 * bf_hi(mine) <= SAFE_BOUND_SQ)) lower_limit(sb, lane);
                    mbar_arrive(sb + BAR_KVF + lane * 8);
                }
                armed = t;
            };
            const bool elected = lane == 0;
#pragma unroll 1
            for (uint32_t it = 0; t < KV_SLOTS; it++) {
                const unsigned long long v = ld_flag();
                if (!have_q) {
                    uint32_t ok;
                    asm volatile("{\n.reg .pred p;\nmbarrier.test_wait.parity.shared::cta.b64 p, [%1], 0;\nselp.u32 %0, 1, 0, p;\n}\n" : "=r"(ok) : "r"(sb + BAR_NRM) : "memory");
                    if (__all_sync(0xffffffffu, ok)) { have_q = true; cta_norms<4>(sb + OFF_QN, q0, q1); }
                }
                if (have_q && armed < t) arm();
                if (seen(v)) {
                    fence_acquire();
                    fence_async();
                    uint32_t avail = ready & todo;
                    do {
                        const int tile = __ffs(avail) - 1;
                        if (t == 4) mbar_wait(sb + BAR_B1D, 0);
                        if (elected) load_tile(t, tile);
                        const uint32_t tn = __shfl_sync(0xffffffffu, nb, tile);
                        if (lane == t) mine = tn;
                        avail &= avail - 1; todo &= ~(1u << tile);
                        t++;
                        if (have_q) arm();
                    } while (avail != 0 && t < KV_SLOTS);
                }
                __syncwarp();
                if (it > (1u << 21)) __trap();
            }
            if (lane == 0) mbar_arrive(sb + BAR_GO);
            if (!have_q) { mbar_wait(sb + BAR_NRM, 0); cta_norms<4>(sb + OFF_QN, q0, q1); }
            arm();
            __syncwarp();
            if ((ready & todo) != todo) {
                seen(ld_flag());
                fence_acquire();
                fence_async();
            }
            if (lane == 0) mbar_wait_bg(sb + BAR_PUB, 0);
            int slot = 0; uint32_t epar = 0;
#pragma unroll 1
            for (; t < 32; t++) {
                if ((ready & todo) == 0) poll_some();
                const int tile = __ffs(ready & todo) - 1;
                todo &= ~(1u << tile);
                const uint32_t tn = __shfl_sync(0xffffffffu, nb, tile);
                if (lane == 0) {
                    mbar_wait_bg(sb + BAR_KVE + slot * 8, slot == KV_SLOTS - 1 ? epar ^ 1 : epar);
                    load_tile(slot, tile);
                    if (!(q0 * bf_lo(tn) <= SAFE_BOUND_SQ && q1 * bf_hi(tn) <= SAFE_BOUND_SQ)) lower_limit(sb, t);
                    mbar_arrive(sb + BAR_KVF + slot * 8);
                }
                __syncwarp();
                if (++slot == KV_SLOTS) { slot = 0; epar ^= 1; }
            }
            if (lane == 0) {
                mbar_wait_bg(sb + BAR_KVE + 2 * 8, 0);
                mbar_arrive(sb + BAR_KVF + 2 * 8);
            }
            const unsigned int* oflags = g_boflag + (r * 2 + half) * 32;
            const int ocol = lane * 64, orow = SEQ + r * 128 + half * 64;
            if (lane < 7) mbar_expect(sb + BAR_OBF + lane * 8, 8192);
            mbar_wait_bg(sb + BAR_KVE + 3 * 8, 0); mbar_wait_bg(sb + BAR_KVE + 4 * 8, 0); mbar_wait_bg(sb + BAR_KVE + 5 * 8, 1);
            {
                auto ld = [&]() { uint32_t v; asm volatile("ld.relaxed.gpu.global.u32 %0, [%1];" : "=r"(v) : "l"(oflags) : "memory"); return v; };
                for (uint32_t n = 0; !__all_sync(0xffffffffu, (int32_t)(ld() - e1 * 8) >= 0); n++) {
                    if (n > (1u << 21)) __trap();
                }
            }
            fence_acquire();
            fence_async();
            if (lane < 7) tma_load(sb + OFF_OB + lane * 8192, &maps.oLd, ocol, orow, sb + BAR_OBF + lane * 8);
        } else if ((tid >> 5) == 15) {
            const int lane = tid & 31;
            mbar_wait_bg(sb + BAR_EPO, 0);
            mbar_wait_bg(sb + BAR_X1, 0);
            const uint32_t e1 = lds_u(sb + OFF_EPOCH);
            if (lane == 0) {
                bulk_store(g_akv + (hp * 16 + r) * 512, sb + OFF_KVB, 8192);
                bulk_commit(); bulk_wait_all();
                red_after_bulk(&g_akvflag[hp]);
                wait_count(&g_akvflag[hp], e1 * 16);
            }
            __syncwarp();
            const float4* src = g_akv + hp * 16 * 512 + r * 32 + lane;
            float4 y = make_float4(0.f, 0.f, 0.f, 0.f);
#pragma unroll 1
            for (int i = 0; i < 4; i++, src += 2048) {
                const float4 x0 = __ldcg(src), x1 = __ldcg(src + 512), x2 = __ldcg(src + 1024), x3 = __ldcg(src + 1536);
                y.x += (x0.x + x1.x) + (x2.x + x3.x); y.y += (x0.y + x1.y) + (x2.y + x3.y);
                y.z += (x0.z + x1.z) + (x2.z + x3.z); y.w += (x0.w + x1.w) + (x2.w + x3.w);
            }
            g_akv2[hp * 512 + r * 32 + lane] = make_uint2(pack(y.x, y.y), pack(y.z, y.w));
            __syncwarp();
            if (lane == 0) {
                red_release(&g_akv2flag[hp]);
                wait_count(&g_akv2flag[hp], e1 * 16);
                fence_async();
                mbar_expect(sb + BAR_Y2, 4096);
                bulk_load(sb + OFF_AV, g_akv2 + hp * 512, 4096, sb + BAR_Y2);
            }
        } else if (tid == 416) {
            mbar_wait_bg(sb + BAR_EPO, 0);
            const uint32_t e1 = lds_u(sb + OFF_EPOCH);
            mbar_wait_bg(sb + BAR_B1D, 0);
            mbar_wait_bg(sb + BAR_NRM, 0);
            mbar_wait_bg(sb + BAR_KVF + 4 * 8, 0);
            int st = 0; uint32_t epar = 1;
#pragma unroll 1
            for (int i = 0; i < 21; i++) {
                const int part = i / 7, kb = i - part * 7;
                const int col = (part == 2 ? 0 : (part + 1) * DM) + wcol;
                const uint32_t base = sb + OFF_A + st * A_STAGE, bar = sb + BAR_AF + st * 8;
                mbar_wait_bg(sb + BAR_AE + st * 8, epar);
                mbar_expect(bar, A_STAGE);
                tma_load(base, &maps.xA, kb * 64, r * 128, bar);
                tma_load(base + 16384, &maps.wA, col, kb * 64, bar);
                if (++st == 3) { st = 0; epar ^= 1; }
            }
            wait_count(&g_aoflag[r], e1 * 8);
            fence_async();
#pragma unroll 1
            for (int kb = 0; kb < 7; kb++) {
                const uint32_t base = sb + OFF_A + st * A_STAGE, bar = sb + BAR_AF + st * 8;
                mbar_wait_bg(sb + BAR_AE + st * 8, epar);
                mbar_expect(bar, A_STAGE);
                tma_load(base, &maps.oLd, kb * 64, r * 128 + half * 64, bar);
                tma_load(base + 8192, &maps.woA, cq * 112, kb * 64, bar);
                tma_load(base + 16384, &maps.woA, cq * 112 + 64, kb * 64, bar);
                if (++st == 3) { st = 0; epar ^= 1; }
            }
            mbar_wait_bg(sb + BAR_ADONE, 0);
            mbar_expect(sb + BAR_WOB, 7 * 16384);
#pragma unroll 1
            for (int kb = 0; kb < 7; kb++) {
                tma_load(sb + OFF_A + kb * 16384, &maps.woB, cq * 112, kb * 64, sb + BAR_WOB);
                tma_load(sb + OFF_A + kb * 16384 + 8192, &maps.woB, cq * 112 + 64, kb * 64, sb + BAR_WOB);
            }
        }
    }
}

typedef CUresult (*EncodeFn)(CUtensorMap*, CUtensorMapDataType, cuuint32_t, void*, const cuuint64_t*, const cuuint64_t*,
                             const cuuint32_t*, const cuuint32_t*, CUtensorMapInterleave, CUtensorMapSwizzle,
                             CUtensorMapL2promotion, CUtensorMapFloatOOBfill);

void make_map(EncodeFn fn, CUtensorMap* m, const void* ptr, uint64_t cols, uint64_t rows, uint32_t box_cols, uint32_t box_rows, bool swz) {
    cuuint64_t dims[2] = {cols, rows};
    cuuint64_t strides[1] = {cols * 2};
    cuuint32_t box[2] = {box_cols, box_rows};
    cuuint32_t es[2] = {1, 1};
    fn(m, CU_TENSOR_MAP_DATA_TYPE_BFLOAT16, 2, const_cast<void*>(ptr), dims, strides, box, es, CU_TENSOR_MAP_INTERLEAVE_NONE,
       swz ? CU_TENSOR_MAP_SWIZZLE_128B : CU_TENSOR_MAP_SWIZZLE_NONE, CU_TENSOR_MAP_L2_PROMOTION_L2_128B, CU_TENSOR_MAP_FLOAT_OOB_FILL_NONE);
}

}

extern "C" void kernel_launch(void* const* d_in, const int* in_sizes, int n_in, void* d_out, int out_size) {
    (void)in_sizes; (void)n_in; (void)out_size;
    EncodeFn fn = nullptr;
    cudaDriverEntryPointQueryResult qr;
    cudaGetDriverEntryPoint("cuTensorMapEncodeTiled", reinterpret_cast<void**>(&fn), cudaEnableDefault, &qr);
    void* o_ptr = nullptr;
    cudaGetSymbolAddress(&o_ptr, g_o);
    Maps maps;
    make_map(fn, &maps.xA, d_in[0], DM, SEQ, 64, 128, true);
    make_map(fn, &maps.wA, d_in[1], 3 * DM, DM, 64, 64, true);
    make_map(fn, &maps.woA, d_in[2], DM, DM, 64, 64, true);
    make_map(fn, &maps.xB, d_in[3], DM, SEQ, 64, 128, true);
    {
        cuuint64_t dims[3] = {DM, DM, 3};
        cuuint64_t strides[2] = {3 * DM * 2, DM * 2};
        cuuint32_t box[3] = {64, 64, 3};
        cuuint32_t es[3] = {1, 1, 1};
        fn(&maps.wB, CU_TENSOR_MAP_DATA_TYPE_BFLOAT16, 3, d_in[4], dims, strides, box, es, CU_TENSOR_MAP_INTERLEAVE_NONE,
           CU_TENSOR_MAP_SWIZZLE_128B, CU_TENSOR_MAP_L2_PROMOTION_L2_128B, CU_TENSOR_MAP_FLOAT_OOB_FILL_NONE);
    }
    make_map(fn, &maps.woB, d_in[5], DM, DM, 64, 64, true);
    make_map(fn, &maps.oLd, o_ptr, DM, 2 * SEQ, 64, 64, true);
    make_map(fn, &maps.oSt, o_ptr, DM, 2 * SEQ, 56, 64, false);
    make_map(fn, &maps.out, d_out, 2 * DM, SEQ, 112, 64, false);
    cudaFuncSetAttribute(fused_kernel, cudaFuncAttributeMaxDynamicSharedMemorySize, SMEM_BYTES);
    fused_kernel<<<NCTA, 512, SMEM_BYTES>>>(maps);
}
```
